```python
import torch

def _softmax(x, axis=-1):
    return torch.softmax(x, dim=axis)
def _gelu(x):
    return torch.nn.functional.gelu(x, approximate="tanh")
def _silu(x):
    return torch.nn.functional.silu(x)
def _sigmoid(x):
    return torch.sigmoid(x)
def _layernorm(x, axis=-1, eps=1e-5):
    m = x.mean(dim=axis, keepdim=True)
    v = x.var(dim=axis, keepdim=True, unbiased=False)
    return (x - m) / torch.sqrt(v + eps)
def _scatter_add(tgt, idx, src, axis=0):
    return tgt.clone().index_add_(axis, idx, src)
def _segment_sum(src, seg, n):
    out = torch.zeros((n,) + src.shape[1:], dtype=src.dtype)
    return out.index_add_(0, seg, src)
def _pad(x, pw):
    flat = tuple(v for pair in reversed(pw) for v in pair)
    return torch.nn.functional.pad(x, flat)

kernel_name = 'concat_heads__mha_block_cached__mha_block_cached__near_ridge'

def setup_inputs():

    _w = (lambda a: (lambda t: t.to(torch.bfloat16) if t.is_floating_point() else t)(torch.as_tensor(a)))
    def _A_setup():
        B, Sq, D = 16, 224, 640
        H, Sk, Dh = 32, 1024, 128
        return {
            "x": _w((lambda *s: torch.randn(*s, dtype=torch.bfloat16) * 0.8)(B, Sq, D)),
            "k_cache": _w((lambda *s: torch.randn(*s, dtype=torch.bfloat16) * 0.8)(B, H, Sk, Dh)),
            "v_cache": _w((lambda *s: torch.randn(*s, dtype=torch.bfloat16) * 0.05)(B, H, Sk, Dh)),
            "wq": _w((lambda *s: torch.randn(*s, dtype=torch.bfloat16) * 0.8)(D, H * Dh) * (D ** -0.5)),
            "wo": _w((lambda *s: torch.randn(*s, dtype=torch.bfloat16) * 0.05)(H * Dh, D) * ((H * Dh) ** -0.5)),
        }
    _A_in = _A_setup()

    def _B_setup():
        B, Sq, D = 16, 224, 640
        H, Sk, Dh = 32, 1024, 128
        return {
            "x": _w((lambda *s: torch.randn(*s, dtype=torch.bfloat16) * 0.8)(B, Sq, D)),
            "k_cache": _w((lambda *s: torch.randn(*s, dtype=torch.bfloat16) * 0.8)(B, H, Sk, Dh)),
            "v_cache": _w((lambda *s: torch.randn(*s, dtype=torch.bfloat16) * 0.05)(B, H, Sk, Dh)),
            "wq": _w((lambda *s: torch.randn(*s, dtype=torch.bfloat16) * 0.8)(D, H * Dh) * (D ** -0.5)),
            "wo": _w((lambda *s: torch.randn(*s, dtype=torch.bfloat16) * 0.05)(H * Dh, D) * ((H * Dh) ** -0.5)),
        }
    _B_in = _B_setup()

    return {
        "A_x": _A_in["x"],
        "A_k_cache": _A_in["k_cache"],
        "A_v_cache": _A_in["v_cache"],
        "A_wq": _A_in["wq"],
        "A_wo": _A_in["wo"],
        "B_x": _B_in["x"],
        "B_k_cache": _B_in["k_cache"],
        "B_v_cache": _B_in["v_cache"],
        "B_wq": _B_in["wq"],
        "B_wo": _B_in["wo"],
    }

def reference(A_x, A_k_cache, A_v_cache, A_wq, A_wo, B_x, B_k_cache, B_v_cache, B_wq, B_wo):
    def _A_ref(x, k_cache, v_cache, wq, wo):
        B, Sq, D = x.shape
        H, Dh = 32, 128
        q = (lambda x, *d: x.permute(*d))((x @ wq).reshape(B, Sq, H, Dh), 0, 2, 1, 3)
        scores = torch.einsum("bhqd,bhkd->bhqk", q, k_cache) * (Dh ** -0.5)
        p = _softmax(scores, axis=-1)
        o = torch.einsum("bhqk,bhkd->bhqd", p, v_cache)
        return (lambda x, *d: x.permute(*d))(o, 0, 2, 1, 3).reshape(B, Sq, H * Dh) @ wo

    def _B_ref(x, k_cache, v_cache, wq, wo):
        B, Sq, D = x.shape
        H, Dh = 32, 128
        q = (lambda x, *d: x.permute(*d))((x @ wq).reshape(B, Sq, H, Dh), 0, 2, 1, 3)
        scores = torch.einsum("bhqd,bhkd->bhqk", q, k_cache) * (Dh ** -0.5)
        p = _softmax(scores, axis=-1)
        o = torch.einsum("bhqk,bhkd->bhqd", p, v_cache)
        return (lambda x, *d: x.permute(*d))(o, 0, 2, 1, 3).reshape(B, Sq, H * Dh) @ wo

    a = _A_ref(A_x, A_k_cache, A_v_cache, A_wq, A_wo)
    b = _B_ref(B_x, B_k_cache, B_v_cache, B_wq, B_wo)
    return torch.concatenate([a, b], axis=-1)
```

```cpp
#include <cuda_runtime.h>
#include <cuda_bf16.h>
#include <cuda.h>
#include <stdint.h>

namespace {

constexpr int kB = 16, kSq = 224, kD = 640, kH = 32, kSk = 1024, kDh = 128;
constexpr int kGroups = 2 * kB;
constexpr int kAttnUnits = kGroups * kH / 2;
constexpr int kOutUnits = kGroups * 5 / 2;
constexpr int kUnits = kAttnUnits + kOutUnits;
constexpr int kMaxUnits = kUnits + 64;
constexpr int kMaxPairs = 72;
constexpr int NQ = 112;
constexpr int PANEL = NQ * 128;
constexpr float kQScale = 0.08838834764831845f * 1.4426950408889634f;
constexpr int SLOT = 16384;
constexpr int NSLOT = 7;

constexpr int SM_PANEL = 0;
constexpr int SM_RING = SM_PANEL + 8 * PANEL;
constexpr int NBAR = NSLOT + 8;
constexpr int SM_ONES = SM_RING + NSLOT * SLOT;
constexpr int SM_BAR = SM_ONES + 9 * 128;
constexpr int SM_END = SM_BAR + 8 * (2 * NBAR + 12) + 32;
constexpr int SMEM_BYTES = SM_END + 1024;
static_assert(SM_RING % 1024 == 0 && PANEL % 1024 == 0, "swizzle alignment");
static_assert(SMEM_BYTES <= 232448, "smem");

struct Params {
  CUtensorMap x[2], wq[2], k[2], v[2], wo[2];
  CUtensorMap o_ld, out;
  const __nv_bfloat16* xp[2];
  const __nv_bfloat16* wp[2];
  const __nv_bfloat16* kp[2];
  const __nv_bfloat16* vp[2];
  uint32_t head[kMaxPairs];
  uint16_t unit[kMaxUnits];
  uint16_t blk[kAttnUnits];
};

struct Unit {
  bool attn, mc;
  int g, hc;
  int h0, nslab;
};
__device__ __forceinline__ int unit_slabs(uint32_t u) {
  return (u & 0x8000u) ? 4 * ((u & 15) + 1 - ((u >> 4) & 15)) : kD / 64;
}
__device__ __forceinline__ bool unit_partial_in(uint32_t u) { return (u & 0x8000u) && (u & 0xF0u); }
__device__ __forceinline__ bool unit_partial_out(uint32_t u) { return (u & 0x8000u) && (u & 15) != 15; }
__device__ __forceinline__ Unit decode_unit(uint32_t u, uint32_t rank) {
  Unit r;
  r.attn = !(u & 0x8000u);
  r.nslab = unit_slabs(u);
  if (r.attn) {
    r.g = (u >> 4) & 31;
    r.hc = (u & 15) * 2 + rank;
    r.mc = true;
    r.h0 = 0;
  } else {
    const uint32_t t = (u >> 8) & 3;
    r.mc = t < 2;
    r.g = ((u >> 10) & 31) + (t < 2 ? 0 : rank);
    r.hc = t < 2 ? 2 * t + rank : 4;
    r.h0 = (u >> 4) & 15;
  }
  return r;
}

__device__ float4 g_part[128 * 2 * 2 * 28 * 128];
__device__ uint4 g_qrow[2 * kMaxPairs * 2 * 16 * 128];
__device__ unsigned int g_pc[128 * 16];
__device__ __nv_bfloat16 g_o[(size_t)kGroups * kSq * kH * kDh];
__device__ unsigned int g_ticket;
__device__ unsigned int g_rd[kAttnUnits];
__device__ unsigned int g_cnt[kAttnUnits];

constexpr int CREGS = 232, SM_OFF = -2, Q_PIN = 0x15, ST_ROWS = 56;
template <bool V>
struct BoolC {
  static constexpr bool value = V;
};
template <int V>
struct IntC {
  static constexpr int value = V;
};
template <int I, int N, class F>
__device__ __forceinline__ void static_for(F&& f) {
  if constexpr (I < N) {
    f(IntC<I>{});
    static_for<I + 1, N>(f);
  }
}
constexpr uint32_t kPat0 = 04321432100, kPat1 = 04302102100;
__host__ __device__ constexpr int x_pos(int pat, int k) { return ((pat == 0 ? kPat0 : kPat1) >> 3 * k) & 7; }
__host__ __device__ constexpr int x_off(int pat, int k) { return k == 0 ? 0 : x_off(pat, k - 1) + (x_pos(pat, k - 1) == 0 ? 3 : 1); }
__host__ __device__ constexpr int w_cut(int i) { return i <= 2 ? 10 * i : 2 + 9 * i; }
__device__ __forceinline__ uint32_t unit_pattern(uint32_t u, uint32_t prev) {
  return !(u & 0x8000u) && (prev & 0x800Fu) == 0x800Fu ? kPat1 : kPat0;
}
__device__ __forceinline__ uint32_t next_pos(uint32_t pos, int k, uint32_t pat) {
  return k < 9 ? (pat >> (3 * k + 3)) & 7 : pos == 4 ? 0 : pos + 1;
}
__device__ __forceinline__ uint32_t pick(bool c, uint32_t a, uint32_t b) {
  uint32_t r;
  asm("{\n.reg .pred p;\nsetp.ne.u32 p, %1, 0;\nselp.u32 %0, %2, %3, p;\n}" : "=r"(r) : "r"((uint32_t)c), "r"(a), "r"(b));
  return r;
}
__device__ __forceinline__ uint32_t ring_round(uint32_t i) { return (i * 9363u) >> 16; }
__device__ __forceinline__ uint32_t ring_slot(uint32_t i) { return i - NSLOT * ring_round(i); }
__device__ __forceinline__ uint32_t ring_par(uint32_t i) { return ring_round(i) & 1; }

__device__ __forceinline__ uint32_t smem_u32(const void* p) { return (uint32_t)__cvta_generic_to_shared(p); }
__device__ __forceinline__ void mbar_init(uint32_t bar, uint32_t cnt) {
  asm volatile("mbarrier.init.shared::cta.b64 [%0], %1;" ::"r"(bar), "r"(cnt));
}
__device__ __forceinline__ void mbar_expect_tx(uint32_t bar, uint32_t bytes) {
  asm volatile("mbarrier.arrive.expect_tx.shared::cta.b64 _, [%0], %1;" ::"r"(bar), "r"(bytes) : "memory");
}
__device__ __forceinline__ void mbar_arrive_n(uint32_t bar, uint32_t n) {
  asm volatile("mbarrier.arrive.shared::cta.b64 _, [%0], %1;" ::"r"(bar), "r"(n) : "memory");
}
__device__ __forceinline__ void mbar_arrive1_if(uint32_t bar, bool pred) {
  asm volatile("{\n.reg .pred p;\nsetp.ne.u32 p, %1, 0;\n@p mbarrier.arrive.shared::cta.b64 _, [%0];\n}" ::"r"(bar), "r"((uint32_t)pred)
               : "memory");
}
__device__ __forceinline__ void mbar_wait(uint32_t bar, uint32_t parity) {
  asm volatile(
      "{\n.reg .pred p;\n.reg .u32 c;\n"
      "mbarrier.try_wait.parity.shared::cta.b64 p, [%0], %1;\n"
      "@p bra DONE;\n"
      "mov.u32 c, 0;\n"
      "SPIN:\n"
      "mbarrier.try_wait.parity.shared::cta.b64 p, [%0], %1;\n"
      "@p bra DONE;\n"
      "add.u32 c, c, 1;\n"
      "setp.gt.u32 p, c, 0x1000000;\n"
      "@p trap;\n"
      "bra SPIN;\n"
      "DONE:\n}" ::"r"(bar),
      "r"(parity)
      : "memory");
}
__device__ __forceinline__ void mbar_wait_warp(uint32_t bar, uint32_t parity) {
  asm volatile(
      "{\n.reg .pred p, q;\n.reg .u32 c;\n"
      "mov.u32 c, 0;\n"
      "SPIN:\n"
      "mbarrier.try_wait.parity.shared::cta.b64 p, [%0], %1;\n"
      "vote.sync.all.pred q, p, 0xffffffff;\n"
      "@q bra.uni DONE;\n"
      "add.u32 c, c, 1;\n"
      "setp.gt.u32 q, c, 0x1000000;\n"
      "@q trap;\n"
      "bra.uni SPIN;\n"
      "DONE:\n}" ::"r"(bar),
      "r"(parity)
      : "memory");
}
__device__ __forceinline__ uint32_t mbar_test(uint32_t bar, uint32_t parity) {
  uint32_t ok;
  asm volatile(
      "{\n.reg .pred p;\nmbarrier.test_wait.parity.shared::cta.b64 p, [%1], %2;\nselp.u32 %0, 1, 0, p;\n}"
      : "=r"(ok)
      : "r"(bar), "r"(parity)
      : "memory");
  return ok;
}
__device__ __forceinline__ uint32_t mbar_test_if(uint32_t bar, uint32_t parity, bool pred) {
  uint32_t ok;
  asm volatile(
      "{\n.reg .pred p, q;\nsetp.ne.u32 q, %3, 0;\nsetp.eq.u32 p, %3, 0;\n"
      "@q mbarrier.test_wait.parity.shared::cta.b64 p, [%1], %2;\nselp.u32 %0, 1, 0, p;\n}"
      : "=r"(ok)
      : "r"(bar), "r"(parity), "r"((uint32_t)pred)
      : "memory");
  return ok;
}
__device__ __forceinline__ void flag_wait(const unsigned int* p, uint32_t target) {
  asm volatile(
      "{\n.reg .pred p;\n.reg .u32 c, v;\n"
      "mov.u32 c, 0;\n"
      "SPIN:\n"
      "ld.acquire.gpu.global.u32 v, [%0];\n"
      "setp.ge.u32 p, v, %1;\n"
      "@p bra DONE;\n"
      "add.u32 c, c, 1;\n"
      "setp.gt.u32 p, c, 0x1000000;\n"
      "@p trap;\n"
      "bra SPIN;\n"
      "DONE:\n}" ::"l"(p),
      "r"(target)
      : "memory");
}
__device__ __forceinline__ void tma_ld2(uint32_t dst, const CUtensorMap* m, int c0, int c1, uint32_t bar, uint64_t pol) {
  asm volatile(
      "cp.async.bulk.tensor.2d.shared::cluster.global.mbarrier::complete_tx::bytes.L2::cache_hint [%0], [%1, {%3, %4}], "
      "[%2], %5;" ::"r"(dst),
      "l"(m), "r"(bar), "r"(c0), "r"(c1), "l"(pol)
      : "memory");
}
__device__ __forceinline__ void tma_ld2_mc(uint32_t dst, const CUtensorMap* m, int c0, int c1, uint32_t bar, uint64_t pol) {
  asm volatile(
      "cp.async.bulk.tensor.2d.shared::cluster.global.mbarrier::complete_tx::bytes.multicast::cluster.L2::cache_hint "
      "[%0], [%1, {%3, %4}], [%2], %5, %6;" ::"r"(dst),
      "l"(m), "r"(bar), "r"(c0), "r"(c1), "h"((uint16_t)3), "l"(pol)
      : "memory");
}
__device__ __forceinline__ void tma_ld3(uint32_t dst, const CUtensorMap* m, int c0, int c1, int c2, uint32_t bar) {
  asm volatile(
      "cp.async.bulk.tensor.3d.shared::cluster.global.mbarrier::complete_tx::bytes [%0], [%1, {%3, %4, %5}], [%2];" ::"r"(dst),
      "l"(m), "r"(bar), "r"(c0), "r"(c1), "r"(c2)
      : "memory");
}
__device__ __forceinline__ void tma_ld3_hint(uint32_t dst, const CUtensorMap* m, int c0, int c1, int c2, uint32_t bar,
                                             uint64_t pol) {
  asm volatile(
      "cp.async.bulk.tensor.3d.shared::cluster.global.mbarrier::complete_tx::bytes.L2::cache_hint [%0], [%1, {%3, %4, "
      "%5}], [%2], %6;" ::"r"(dst),
      "l"(m), "r"(bar), "r"(c0), "r"(c1), "r"(c2), "l"(pol)
      : "memory");
}
__device__ __forceinline__ void tma_st3(const CUtensorMap* m, int c0, int c1, int c2, uint32_t src) {
  asm volatile("cp.async.bulk.tensor.3d.global.shared::cta.bulk_group [%0, {%2, %3, %4}], [%1];" ::"l"(m), "r"(src),
               "r"(c0), "r"(c1), "r"(c2)
               : "memory");
}
__device__ __forceinline__ void wgmma_fence() { asm volatile("wgmma.fence.sync.aligned;" ::: "memory"); }
__device__ __forceinline__ void wgmma_commit() { asm volatile("wgmma.commit_group.sync.aligned;" ::: "memory"); }
template <int N>
__device__ __forceinline__ void wgmma_wait() {
  asm volatile("wgmma.wait_group.sync.aligned %0;" ::"n"(N) : "memory");
}
template <int N>
__device__ __forceinline__ void wgmma_wait_pin(int never, int c) {
  asm volatile("{\n.reg .pred p;\nsetp.eq.u32 p, %1, %2;\nAGAIN:\nwgmma.wait_group.sync.aligned %0;\n@p bra.uni AGAIN;\n}" ::"n"(N),
               "r"(never), "r"(c)
               : "memory");
}
__device__ __forceinline__ void pin_order(int never, int c) {
  asm volatile("{\n.reg .pred p;\nsetp.eq.u32 p, %0, %1;\nAGAIN:\n@p nanosleep.u32 1;\n@p bra.uni AGAIN;\n}" ::"r"(never), "r"(c) : "memory");
}
template <int N>
__device__ __forceinline__ void fence_regs(float (&d)[N]) {
#pragma unroll
  for (int i = 0; i < N; i++) asm volatile("" : "+f"(d[i])::"memory");
}
__device__ __forceinline__ void fence_async_smem() { asm volatile("fence.proxy.async.shared::cta;" ::: "memory"); }
__device__ __forceinline__ void bar_sync(int id, int n) { asm volatile("bar.sync %0, %1;" ::"r"(id), "r"(n) : "memory"); }
__device__ __forceinline__ void bar_arrive(int id, int n) {
  asm volatile("bar.arrive %0, %1;" ::"r"(id), "r"(n) : "memory");
}
__device__ __forceinline__ void stsm_x4_t(uint32_t addr, uint32_t r0, uint32_t r1, uint32_t r2, uint32_t r3) {
  asm volatile("stmatrix.sync.aligned.m8n8.x4.trans.shared.b16 [%0], {%1, %2, %3, %4};" ::"r"(addr), "r"(r0), "r"(r1),
               "r"(r2), "r"(r3)
               : "memory");
}
__device__ __forceinline__ void stsm_x4_t_pin(uint32_t addr, uint32_t r0, uint32_t r1, uint32_t r2, uint32_t r3, int never, int c) {
  asm volatile(
      "{\n.reg .pred p;\nsetp.eq.u32 p, %5, %6;\nAGAIN:\n"
      "stmatrix.sync.aligned.m8n8.x4.trans.shared.b16 [%0], {%1, %2, %3, %4};\n@p bra.uni AGAIN;\n}" ::"r"(addr),
      "r"(r0), "r"(r1), "r"(r2), "r"(r3), "r"(never), "r"(c)
      : "memory");
}
__device__ __forceinline__ uint32_t pack_bf16(float lo, float hi) {
  uint32_t r;
  asm("cvt.rn.bf16x2.f32 %0, %1, %2;" : "=r"(r) : "f"(hi), "f"(lo));
  return r;
}
__device__ __forceinline__ float ex2(float x) {
  float y;
  asm("ex2.approx.ftz.f32 %0, %1;" : "=f"(y) : "f"(x));
  return y;
}
__device__ __forceinline__ uint32_t mk_desc(uint32_t addr) { return (1u << 16) | ((addr & 0x3FFFFu) >> 4); }

template <int TA, int TB = 0>
__device__ __forceinline__ void wgmma_n112(float (&d)[56], uint32_t descA, uint32_t descB, int scaleD) {
  asm volatile(
      "{\n.reg .pred p;\n.reg .b32 hi, hb;\n.reg .b64 da, db;\nsetp.ne.b32 p, %58, 0;\n"
      "mov.b32 hi, 0x40000040;\nmov.b32 hb, %61;\nmov.b64 da, {%56, hi};\nmov.b64 db, {%57, hb};\n"
      "wgmma.mma_async.sync.aligned.m64n112k16.f32.bf16.bf16 "
      "{%0, %1, %2, %3, %4, %5, %6, %7, %8, %9, %10, %11, %12, %13, "
      "%14, %15, %16, %17, %18, %19, %20, %21, %22, %23, %24, %25, %26, %27, "
      "%28, %29, %30, %31, %32, %33, %34, %35, %36, %37, %38, %39, %40, %41, "
      "%42, %43, %44, %45, %46, %47, %48, %49, %50, %51, %52, %53, %54, %55}, "
      "da, db, p, 1, 1, %59, %60;\n}\n"
      : "+f"(d[0]), "+f"(d[1]), "+f"(d[2]), "+f"(d[3]), "+f"(d[4]), "+f"(d[5]), "+f"(d[6]),
        "+f"(d[7]), "+f"(d[8]), "+f"(d[9]), "+f"(d[10]), "+f"(d[11]), "+f"(d[12]), "+f"(d[13]),
        "+f"(d[14]), "+f"(d[15]), "+f"(d[16]), "+f"(d[17]), "+f"(d[18]), "+f"(d[19]), "+f"(d[20]),
        "+f"(d[21]), "+f"(d[22]), "+f"(d[23]), "+f"(d[24]), "+f"(d[25]), "+f"(d[26]), "+f"(d[27]),
        "+f"(d[28]), "+f"(d[29]), "+f"(d[30]), "+f"(d[31]), "+f"(d[32]), "+f"(d[33]), "+f"(d[34]),
        "+f"(d[35]), "+f"(d[36]), "+f"(d[37]), "+f"(d[38]), "+f"(d[39]), "+f"(d[40]), "+f"(d[41]),
        "+f"(d[42]), "+f"(d[43]), "+f"(d[44]), "+f"(d[45]), "+f"(d[46]), "+f"(d[47]), "+f"(d[48]),
        "+f"(d[49]), "+f"(d[50]), "+f"(d[51]), "+f"(d[52]), "+f"(d[53]), "+f"(d[54]), "+f"(d[55])
      : "r"(descA), "r"(descB), "r"(scaleD), "n"(TA), "n"(TB), "n"(TB ? 8 : 0x40000040));
}

__device__ __forceinline__ void wgmma_colsum(float (&d)[28], uint32_t descA, uint32_t descB, int scaleD) {
  asm volatile(
      "{\n.reg .pred p;\n.reg .b32 ha, hb;\n.reg .b64 da, db;\nsetp.ne.b32 p, %30, 0;\n"
      "mov.b32 ha, 8;\nmov.b32 hb, 0x40000040;\nmov.b64 da, {%28, ha};\nmov.b64 db, {%29, hb};\n"
      "wgmma.mma_async.sync.aligned.m64n56k16.f32.bf16.bf16 "
      "{%0, %1, %2, %3, %4, %5, %6, %7, %8, %9, %10, %11, %12, %13, %14, %15, %16, %17, %18, %19, %20, %21, %22, %23, %24, %25, %26, %27}, "
      "da, db, p, 1, 1, 0, 0;\n}\n"
      : "+f"(d[0]), "+f"(d[1]), "+f"(d[2]), "+f"(d[3]), "+f"(d[4]), "+f"(d[5]), "+f"(d[6]), "+f"(d[7]), "+f"(d[8]), "+f"(d[9]), "+f"(d[10]), "+f"(d[11]), "+f"(d[12]), "+f"(d[13]), "+f"(d[14]), "+f"(d[15]), "+f"(d[16]), "+f"(d[17]), "+f"(d[18]), "+f"(d[19]), "+f"(d[20]), "+f"(d[21]), "+f"(d[22]), "+f"(d[23]), "+f"(d[24]), "+f"(d[25]), "+f"(d[26]), "+f"(d[27])
      : "r"(descA), "r"(descB), "r"(scaleD));
}

template <int T>
__device__ __forceinline__ void pack_half(float (&pk)[56], const float (&a)[56], float sc) {
#pragma unroll
  for (int i = 0; i < 28; i++) pk[28 * T + i] = __uint_as_float(pack_bf16(a[2 * i] * sc, a[2 * i + 1] * sc));
}
template <int T>
__device__ __forceinline__ void fence_half(float (&pk)[56]) {
#pragma unroll
  for (int i = 0; i < 28; i++) asm volatile("" : "+f"(pk[28 * T + i])::"memory");
}
template <int T>
__device__ __forceinline__ void store_half(uint32_t addr, const float (&pk)[56]) {
#pragma unroll
  for (int q = 0; q < 7; q++) {
    const float* r = pk + 28 * T + 4 * q;
    stsm_x4_t(addr + T * PANEL + q * 2048, __float_as_uint(r[0]), __float_as_uint(r[1]), __float_as_uint(r[2]), __float_as_uint(r[3]));
  }
}

template <int T>
__device__ __forceinline__ void q_half(uint32_t addr, float (&pk)[56], const float (&a)[56], int never) {
#pragma unroll
  for (int q = 0; q < 7; q++) {
    uint32_t r[4];
#pragma unroll
    for (int i = 0; i < 4; i++) {
      r[i] = pack_bf16(a[8 * q + 2 * i] * kQScale, a[8 * q + 2 * i + 1] * kQScale);
      pk[28 * T + 4 * q + i] = __uint_as_float(r[i]);
    }
    if (q < 6 && (Q_PIN >> q & 1)) stsm_x4_t_pin(addr + T * PANEL + q * 2048, r[0], r[1], r[2], r[3], never, 32 + 2 * (7 * T + q));
    else stsm_x4_t(addr + T * PANEL + q * 2048, r[0], r[1], r[2], r[3]);
  }
}

__device__ __forceinline__ float bf_lo(uint32_t u) { return __uint_as_float(u << 16); }
__device__ __forceinline__ float bf_hi(uint32_t u) { return __uint_as_float(u & 0xFFFF0000u); }

__device__ __forceinline__ void fma8(float* o, float a, const uint4& w, float c) {
  o[0] = fmaf(a, bf_lo(w.x), o[0] * c), o[1] = fmaf(a, bf_hi(w.x), o[1] * c);
  o[2] = fmaf(a, bf_lo(w.y), o[2] * c), o[3] = fmaf(a, bf_hi(w.y), o[3] * c);
  o[4] = fmaf(a, bf_lo(w.z), o[4] * c), o[5] = fmaf(a, bf_hi(w.z), o[5] * c);
  o[6] = fmaf(a, bf_lo(w.w), o[6] * c), o[7] = fmaf(a, bf_hi(w.w), o[7] * c);
}
__device__ __forceinline__ void slow_rows(uint4* qrow, int tq, const __nv_bfloat16* xp, const __nv_bfloat16* wp,
                                          const __nv_bfloat16* kp, const __nv_bfloat16* vp, __nv_bfloat16* op) {
  if (tq >= NQ) return;
#pragma unroll 1
  for (int c = 0; c < 16; c++) {
    float q[8] = {};
#pragma unroll 1
    for (int k = 0; k < kD; k++)
      fma8(q, __bfloat162float(xp[tq * kD + k]), __ldg(reinterpret_cast<const uint4*>(wp + k * (kH * kDh)) + c), 1.f);
    qrow[c * 128] = make_uint4(pack_bf16(q[0] * kQScale, q[1] * kQScale), pack_bf16(q[2] * kQScale, q[3] * kQScale),
                               pack_bf16(q[4] * kQScale, q[5] * kQScale), pack_bf16(q[6] * kQScale, q[7] * kQScale));
  }
#pragma unroll 1
  for (int pass = 0; pass < 4; pass++) {
    float o[32] = {}, m = -INFINITY, l = 0.f;
#pragma unroll 1
    for (int key = 0; key < kSk; key++) {
      const uint4* kr = reinterpret_cast<const uint4*>(kp + key * kDh);
      const uint4* vr = reinterpret_cast<const uint4*>(vp + key * kDh) + 4 * pass;
      float s = 0.f;
#pragma unroll 1
      for (int c = 0; c < 16; c++) {
        const uint4 q = qrow[c * 128], k = __ldg(kr + c);
        s = fmaf(bf_lo(q.x), bf_lo(k.x), s); s = fmaf(bf_hi(q.x), bf_hi(k.x), s);
        s = fmaf(bf_lo(q.y), bf_lo(k.y), s); s = fmaf(bf_hi(q.y), bf_hi(k.y), s);
        s = fmaf(bf_lo(q.z), bf_lo(k.z), s); s = fmaf(bf_hi(q.z), bf_hi(k.z), s);
        s = fmaf(bf_lo(q.w), bf_lo(k.w), s); s = fmaf(bf_hi(q.w), bf_hi(k.w), s);
      }
      const float mn = fmaxf(m, s);
      const float ms = (mn == -INFINITY) ? 0.f : mn;
      const float corr = ex2(m - ms), p = ex2(s - ms);
      l = l * corr + p;
      m = mn;
      const float pb = __bfloat162float(__float2bfloat16(p));
#pragma unroll
      for (int c = 0; c < 4; c++) fma8(o + 8 * c, pb, __ldg(vr + c), corr);
    }
    const float sc = __fdividef(1.f, l);
    __nv_bfloat16* dst = op + (pass >> 1) * PANEL + (pass & 1) * 3584 + (tq >> 3) * 64 + (tq & 7);
#pragma unroll
    for (int d = 0; d < 32; d++) dst[(d >> 3) * 896 + (d & 7) * 8] = __float2bfloat16(o[d] * sc);
  }
}

__device__ __forceinline__ uint32_t launch_epoch() { return atomicAdd(&g_ticket, 1u) / gridDim.x; }

__global__ void __cluster_dims__(2, 1, 1) __launch_bounds__(384, 1) mha_fused_kernel(const __grid_constant__ Params prm) {
  extern __shared__ __align__(1024) unsigned char smem_raw[];

  const uint32_t sb = (smem_u32(smem_raw) + 1023u) & ~1023u;
  const uint32_t full0 = sb + SM_BAR, empty0 = full0 + 8 * NBAR, sfull0 = empty0 + 8 * NBAR;
  const uint32_t cred0 = sfull0 + 32, redo0 = cred0 + 64, epoch_addr = redo0 + 8, go_bar = redo0 + 16, ok_bar = redo0 + 24;
  const uint32_t rank = blockIdx.x & 1, pair = blockIdx.x >> 1;
  const uint32_t head = prm.head[pair];
  const int u_begin = head & 1023, u_end = u_begin + ((head >> 10) & 31);
  const uint32_t delay = ((head >> 15) & 255) * 256;
  const int tid = threadIdx.x;
  const int wid = __shfl_sync(0xffffffffu, tid >> 5, 0), wg = wid >> 2;

  if (wg == 2) {
    asm volatile("setmaxnreg.dec.sync.aligned.u32 %0;" ::"n"(504 - 2 * CREGS));
    const int warp = wid & 3, lane = tid & 31;
    bar_sync(0, 384);
    asm volatile("barrier.cluster.arrive.relaxed.aligned;" ::: "memory");
    if (warp < 3) {
      const uint32_t t0 = (uint32_t)clock();
      while ((uint32_t)clock() - t0 < delay) __nanosleep(100);
    }
    auto slot_addr = [&](uint32_t i) { return sb + SM_RING + ring_slot(i) * SLOT; };
    auto full_bar = [&](uint32_t i) { return full0 + 8 * ring_slot(i); };
    if (warp == 0) {
      if (lane == 0) {
        uint64_t pol;
        asm volatile("createpolicy.fractional.L2::evict_first.b64 %0, 1.0;" : "=l"(pol));
        uint32_t it = 0;
        auto acquire = [&](uint32_t i) { mbar_wait(empty0 + 8 * ring_slot(i), ring_par(i) ^ 1); };
        uint32_t rblk = 0, rleft = 0;
        auto block_read = [&]() {
          asm volatile("red.relaxed.gpu.global.add.u32 [%0], 1;" ::"l"(&g_rd[prm.blk[rblk] & 511]) : "memory");
          rblk++;
          rleft--;
        };
        uint32_t prev = 0;
        for (int ui = u_begin; ui < u_end; ui++) {
          const uint32_t code = ui == u_begin ? head >> 23 : prm.unit[ui], pat = unit_pattern(code, prev);
          prev = code;
          const Unit u = decode_unit(code, rank);
          const int br = u.g >> 4;
          const CUtensorMap* mw = u.attn ? &prm.wq[br] : &prm.wo[br];
          const int nslab = u.nslab;
#pragma unroll 1
          for (int k = 0, pos = 0; k < nslab; k++) {
            const uint32_t i = pos == 0 ? it + 1 : it;
            acquire(i);
            mbar_expect_tx(full_bar(i), SLOT);
            tma_ld3(slot_addr(i), mw, 0, u.h0 * 256 + k * 64, u.hc * 2, full_bar(i));
            while (rleft && k == 2) block_read();
            if (rleft && (k == 10 || (k >= 12 && (k & 3) == 0))) block_read();
            if (!u.attn && k == 4) rblk = u.g * 16 + u.h0, rleft = nslab >> 2;
            it += pos == 0 ? 3 : 1;
            pos = next_pos(pos, k, pat);
          }
          if (u.attn) {
            const int row0 = ((u.g & 15) * kH + u.hc) * kSk;
#pragma unroll 1
            for (int j = 0; j < kSk / 32; j++, it++) {
              acquire(it);
              if (j == kSk / 32 - 2) mbar_arrive_n(go_bar, 1);
              mbar_expect_tx(full_bar(it), SLOT);
              const bool isv = j == 31 || (j > 0 && !(j & 1));
              tma_ld3_hint(slot_addr(it), isv ? &prm.v[br] : &prm.k[br], 0, row0 + (((j + 1) >> 1) - isv) * 64, 0, full_bar(it), pol);
            }
          }
        }
        if (rleft) {
          acquire(it + NSLOT - 1);
          while (rleft) block_read();
        }
      }
    } else if (warp < 3) {
      asm volatile("barrier.cluster.wait.acquire.aligned;" ::: "memory");
      const int w = warp == 1 ? rank : rank ^ 1;
      uint32_t it = 0, nc = 0, pph = 0, go_ph = 0, prev = 0, peer_cred0;
      asm volatile("mapa.shared::cluster.u32 %0, %1, %2;" : "=r"(peer_cred0) : "r"(cred0), "r"(rank ^ 1));
      for (int ui = u_begin; ui < u_end; ui++) {
        const uint32_t code = ui == u_begin ? head >> 23 : prm.unit[ui], pat = unit_pattern(code, prev);
        prev = code;
        Unit u = decode_unit(code, rank);
        const CUtensorMap* mx = u.attn ? &prm.x[u.g >> 4] : &prm.o_ld;
        const int nslab = u.nslab;
        uint32_t oslot = 0;
        if (!u.attn) oslot = prm.blk[u.g * 16 + ((u.h0 + lane) & 15)] & 511;
        const bool polls = !u.attn && (warp == 1 || !u.mc);
        uint32_t epoch1 = 0;
        for (uint32_t spins = 0; polls && epoch1 == 0; spins++) {
          asm volatile("ld.volatile.shared.u32 %0, [%1];" : "=r"(epoch1) : "r"(epoch_addr) : "memory");
          asm volatile("{\n.reg .pred p;\nsetp.gt.u32 p, %0, 0x4000000;\n@p trap;\n}" ::"r"(spins));
        }
        uint32_t ready = 0;
        auto refresh = [&]() {
          uint32_t v = 0;
          if (lane < 16) asm volatile("ld.acquire.gpu.global.u32 %0, [%1];" : "=r"(v) : "l"(&g_cnt[u.g * 16 + lane]) : "memory");
          ready = __ballot_sync(0xffffffffu, lane == 16 || (lane < 16 && v >= 2 * epoch1)) >> u.h0;
          asm volatile("fence.proxy.async.global;" ::: "memory");
        };
        uint64_t xpol;
        if (!u.attn) asm volatile("createpolicy.fractional.L2::evict_first.b64 %0, 1.0;" : "=l"(xpol));
        else asm volatile("createpolicy.fractional.L2::evict_normal.b64 %0, 1.0;" : "=l"(xpol));
        if (polls && unit_partial_in(code)) {
          if (lane == 0) flag_wait(&g_pc[((code >> 8) & 127) * 16 + u.h0 - 1], 2 * epoch1);
          __syncwarp();
        }
        for (int k = 0, pos = 0; k < nslab; k++) {
          if (polls && (k & 3) == 0) {
            for (uint32_t spins = 0; !((ready >> (k >> 2)) & 1); spins++) {
              refresh();
              asm volatile("{\n.reg .pred p;\nsetp.gt.u32 p, %0, 0x400000;\n@p trap;\n}" ::"r"(spins));
            }
          }
          const int xcol = u.attn ? k * 64 : 0;
          const int xrow = (u.attn ? u.g & 15 : __shfl_sync(0xffffffffu, oslot, k >> 2) * 4 + (k & 3)) * kSq + w * NQ;
          uint32_t fbar, dst, par;
          if (pos == 0) {
            const uint32_t i = it + 2 * w;
            fbar = full_bar(i), dst = slot_addr(i), par = ring_par(i);
            it += 3;
          } else {
            const uint32_t q = pos - 1;
            fbar = full0 + 8 * (NSLOT + 4 * w + q), dst = sb + SM_PANEL + (4 * w + q) * PANEL, par = (pph >> q) & 1;
            pph ^= 1u << q;
            it += 1;
          }
          pos = next_pos(pos, k, pat);
          mbar_wait_warp(fbar + 8 * NBAR, par ^ 1);
          if (lane == 0) {
            mbar_expect_tx(fbar, PANEL);
            if (!u.mc) {
              tma_ld2(dst, mx, xcol, xrow, fbar, xpol);
            } else if (warp == 1) {
              if (it > 10) mbar_wait(cred0 + 8 * (nc & 7), (nc >> 3) & 1);
              tma_ld2_mc(dst, mx, xcol, xrow, fbar, xpol);

            } else if (it > 10) {
              asm volatile("mbarrier.arrive.shared::cluster.b64 _, [%0];" ::"r"(peer_cred0 + 8 * (nc & 7)) : "memory");
            }
          }
          __syncwarp();
          if (u.mc && it > 10) nc++;
          if (polls && (k & 3) == 1 && !((ready >> (k >> 2)) & 2)) refresh();
        }
        if (u.attn) {
          mbar_wait_warp(go_bar, go_ph);
          go_ph ^= 1;
          it += kSk / 32;
        }
      }
    } else if (lane == 0) {
      uint32_t ph = 0;
      const uint32_t epoch = launch_epoch();
      asm volatile("st.volatile.shared.u32 [%0], %1;" ::"r"(epoch_addr), "r"(epoch + 1) : "memory");
      for (int ui = u_begin; ui < u_end; ui++, ph ^= 1) {
        const uint32_t code = prm.unit[ui];
        const Unit u = decode_unit(code, rank);
        if (u.attn) {
          const uint32_t blk = prm.blk[code & 511], gen = (blk >> 9) & 7;
          if (gen > 0) flag_wait(&g_rd[blk & 511], 5 * (epoch * (blk >> 12) + gen));
        }
        mbar_arrive_n(ok_bar, 1);
        if (u.attn || unit_partial_out(code)) {
#pragma unroll 1
          for (int q = 0; q < 4; q++) mbar_wait(sfull0 + 8 * q, ph);
          unsigned int* flag = u.attn ? &g_cnt[code & 511] : &g_pc[((code >> 8) & 127) * 16 + (code & 15)];
          asm volatile("red.release.gpu.global.add.u32 [%0], 1;" ::"l"(flag) : "memory");
          continue;
        }
        const int row = (u.g & 15) * kSq, cb = (u.g >> 4) * 10 + u.hc * 2;
#pragma unroll 1
        for (int q = 0; q < 4; q++) {
          const int w = q & 1, t = q >> 1;
          mbar_wait(sfull0 + 8 * q, ph);
          fence_async_smem();
#pragma unroll 1
          for (int r = 0; r < NQ; r += ST_ROWS) {
            tma_st3(&prm.out, 0, row + w * NQ + r, cb + t, sb + SM_PANEL + (4 * w + 2 + t) * PANEL + r * 128);
            asm volatile("cp.async.bulk.commit_group;" ::: "memory");
            if (ui + 1 < u_end) asm volatile("cp.async.bulk.wait_group.read 0;" ::: "memory");
          }
          mbar_arrive_n(empty0 + 8 * (NSLOT + 4 * w + 2 + t), 2);
        }
      }
      asm volatile("cp.async.bulk.wait_group 0;" ::: "memory");
    }
  } else {
    const int tq = tid & 127, lane = tid & 31, warp = tq >> 5;
    if (tid == 0) {
#pragma unroll
      for (int i = 0; i < NBAR; i++) {
        mbar_init(full0 + 8 * i, 1);
        mbar_init(empty0 + 8 * i, 2);
      }
#pragma unroll
      for (int i = 0; i < 12; i++) mbar_init(sfull0 + 8 * i, i < 4 ? 4 : 1);
      mbar_init(go_bar, 1);
      mbar_init(ok_bar, 1);
      asm volatile("st.shared.v4.u32 [%0], {%1, %1, %1, %1};" ::"r"(redo0), "r"(0) : "memory");
      asm volatile("fence.mbarrier_init.release.cluster;" ::: "memory");
    }
    if (tid >= 128 && tq < 72)
      asm volatile("st.shared.v4.u32 [%0], {%1, %1, %1, %1};" ::"r"(sb + SM_ONES + 16 * tq), "r"(tq & 8 ? 0u : 0x3F803F80u) : "memory");
    bar_sync(0, 384);
    asm volatile("barrier.cluster.arrive.relaxed.aligned;" ::: "memory");
    asm volatile("setmaxnreg.inc.sync.aligned.u32 %0;" ::"n"(CREGS));
    const uint32_t stage = sb + SM_PANEL + wg * 4 * PANEL;
    const uint32_t st_q = __shfl_sync(
        0xffffffffu, stage + ((lane >> 4) * 8 + (lane & 7)) * 128 + (((2 * warp + ((lane >> 3) & 1)) ^ (lane & 7)) << 4), lane);
    const uint32_t st_p = st_q + 2 * PANEL;
    const uint32_t dq = mk_desc(stage), dring = mk_desc(sb + SM_RING);
    float acc[2][56], s[56] = {};
    const int never = (sb >> 24) & ~1u;
    uint32_t it = 0, pph = 0;
    auto wait_full = [&](uint32_t i) { mbar_wait_warp(full0 + 8 * ring_slot(i), ring_par(i)); };
    auto test = [&](uint32_t bar, uint32_t par) { return mbar_test_if(bar, par, warp == 0); };
    auto probe = [&](uint32_t i) { return test(full0 + 8 * ring_slot(i), ring_par(i)); };
    auto release = [&](uint32_t i) { mbar_arrive1_if(empty0 + 8 * ring_slot(i), tq == 0); };
    auto slot_desc = [&](uint32_t i) { return dring + ring_slot(i) * (SLOT >> 4); };
    if (wg == 1) bar_arrive(1, 256);

    struct Fin {
      float tot[28];
      uint32_t rp[14], z;
      char* dst;
    };
    constexpr int SUMS = PANEL + PANEL / 2;
    uint32_t ps[14] = {};
    auto step_sums = [&]() {
#pragma unroll
      for (int q = 0; q < 3; q++) stsm_x4_t(st_p + SUMS + q * 2048, ps[2 * q], ps[2 * q + 7], ps[2 * q + 1], ps[2 * q + 8]);
      asm volatile("stmatrix.sync.aligned.m8n8.x2.trans.shared.b16 [%0], {%1, %2};" ::"r"(st_p + SUMS + 3 * 2048), "r"(ps[6]), "r"(ps[13])
                   : "memory");
      fence_async_smem();
    };
    auto step_finite = [&](Fin& f) {
      uint32_t z[4] = {0, 0, 0, 0};
#pragma unroll
      for (int i = 0; i < 28; i++)
        asm volatile("fma.rn.bf16x2 %0, %1, %2, %0;" : "+r"(z[i & 3]) : "r"(__float_as_uint(s[2 * i])), "r"(__float_as_uint(s[2 * i + 1])));
      asm volatile("add.rn.bf16x2 %0, %0, %1;" : "+r"(z[0]) : "r"(z[1]));
      asm volatile("add.rn.bf16x2 %0, %0, %1;" : "+r"(z[2]) : "r"(z[3]));
      asm volatile("add.rn.bf16x2 %0, %1, %2;" : "=r"(f.z) : "r"(z[0]), "r"(z[2]));
    };
    auto issue_colsum = [&](Fin& f) {
#pragma unroll
      for (int i = 0; i < 28; i++) f.tot[i] = 0.f;
#pragma unroll
      for (int kk = 0; kk < 4; kk++)
        wgmma_colsum(f.tot, dring + (7 << 16) + ((SM_ONES - SM_RING) >> 4), dq + ((2 * PANEL + SUMS) >> 4) + 2 * kk, kk > 0);
      wgmma_commit();
    };
    auto step_check = [&](Fin& f, bool live) {
      fence_regs(f.tot);
#pragma unroll
      for (int g = 0; g < 14; g++) {
        const int i = g < 7 ? 4 * g : 4 * (g - 7) + 2;
        float a, b2;
        asm("rcp.approx.ftz.f32 %0, %1;" : "=f"(a) : "f"(f.tot[i]));
        asm("rcp.approx.ftz.f32 %0, %1;" : "=f"(b2) : "f"(f.tot[i + 1]));
        f.rp[g] = pack_bf16(a, b2);
      }
      uint32_t lo = 0x03800380u, hi = 0x53805380u;
#pragma unroll
      for (int g = 0; g < 14; g += 2) lo = __vimin3_u16x2(lo, f.rp[g], f.rp[g + 1]), hi = __vimax3_u16x2(hi, f.rp[g], f.rp[g + 1]);
      const uint32_t bad = (lo ^ 0x03800380u) | (hi ^ 0x53805380u) | (((f.z & 0x7F807F80u) + 0x00800080u) & 0x80008000u);
      asm volatile("{\n.reg .pred p;\nsetp.ne.u32 p, %1, 0;\n@p st.shared.u32 [%0], %1;\n}" ::"r"(redo0 + 4 * wg), "r"(live ? bad : 0)
                   : "memory");
    };
    auto o_base = [&](uint32_t u) {
      return reinterpret_cast<char*>(g_o) + (size_t)((((prm.blk[u & 511] & 511u) * 4 + rank * 2) * 2 + wg) * (uint32_t)PANEL);
    };
    auto step_write = [&](const Fin& f, int lo, int hi) {
#pragma unroll
      for (int i = lo; i < hi; i++) {
        uint32_t v = __float_as_uint(s[i]);
        asm("mul.rn.bf16x2 %0, %0, %1;" : "+r"(v) : "r"(f.rp[(i % 28) >> 1]));
        s[i] = __uint_as_float(v);
        asm volatile("st.global.u32 [%0], %1;" ::"l"(f.dst + (i / 28) * 2 * PANEL + (i & 1) * 1792 + ((i % 28) >> 1) * 128), "r"(v) : "memory");
      }
    };
    auto keep_alive = [&](int lo, int hi, int c) {
      if (never == c) {
#pragma unroll
        for (int i = lo; i < hi; i++) asm volatile("st.shared.f32 [%0], %1;" ::"r"(stage + 4 * i), "f"(s[i]) : "memory");
        pin_order(never, c);
      }
    };
    auto step_signal = [&](int t) {
      __syncwarp();
      mbar_arrive1_if(sfull0 + 8 * (2 * t + wg), lane == 0);
    };
    auto free_panel = [&](int q) { mbar_arrive1_if(empty0 + 8 * (NSLOT + 4 * wg + q), tq < 2); };
    auto read_verdict = [&]() {
      uint32_t redo;
      asm volatile("ld.shared.u32 %0, [%1];" : "=r"(redo) : "r"(redo0 + 4 * wg) : "memory");
      return redo;
    };
    auto step_redo = [&](uint32_t prev) {
      asm volatile("" : "+r"(prev));
      bar_sync(3 + wg, 128);
      if (tq == 0) asm volatile("st.shared.u32 [%0], %1;" ::"r"(redo0 + 4 * wg), "r"(0) : "memory");
      const Unit u = decode_unit(prev & 511, rank);
      const int br = u.g >> 4, b = u.g & 15;
      const size_t off = (size_t)(b * kH + u.hc) * kSk * kDh;
      slow_rows(g_qrow + (blockIdx.x * 2 + wg) * (16 * 128) + tq, tq, prm.xp[br] + (b * kSq + wg * NQ) * kD, prm.wp[br] + u.hc * kDh,
                prm.kp[br] + off, prm.vp[br] + off, reinterpret_cast<__nv_bfloat16*>(o_base(prev)));
#pragma unroll
      for (int i = 0; i < 56; i++) s[i] = 0.f;
    };
    auto issue_slab = [&](uint32_t da, uint32_t db, int accum, auto split, auto tb) {
      constexpr int TB = tb.value, KS = TB ? 224 : 2;
      if (TB) db += 111 << 16;
      if (split.value == 1) {
#pragma unroll
        for (int t = 0; t < 2; t++) {
#pragma unroll
          for (int kk = 0; kk < 4; kk++) {
            if (t == 1 && kk == 2) bar_arrive(2 - wg, 256);
            wgmma_n112<1, TB>(acc[t], da + t * 512 + kk * 128, db + kk * KS, 1);
          }
          wgmma_commit();
        }
      } else {
#pragma unroll
        for (int kk = 0; kk < 4; kk++) {
          if (kk == 3 && split.value == 0) bar_arrive(2 - wg, 256);
          wgmma_n112<1, TB>(acc[0], da + kk * 128, db + kk * KS, kk > 0 ? 1 : accum);
          wgmma_n112<1, TB>(acc[1], da + 512 + kk * 128, db + kk * KS, kk > 0 ? 1 : accum);
        }
        wgmma_commit();
      }
    };

    uint32_t code = head >> 23, prev = 0, pend = 0, uph = 0;
    uint32_t da = slot_desc(1), db = slot_desc(2 * wg);
    auto next_unit = [&](bool block) {
      da = slot_desc(it + 1), db = slot_desc(it + 2 * wg);
      if (block) {
        if (!__all_sync(0xffffffffu, probe(it + 1) & probe(it + 2 * wg))) {
          wait_full(it + 1);
          wait_full(it + 2 * wg);
        }
      }
    };
    wait_full(1);
    wait_full(2 * wg);
    for (int left = (head >> 10) & 31; left > 0; left--) {
      const int ui = u_end - left;
      uint32_t nxt;
      bool defer;
      auto peek = [&]() {
        const uint32_t cur = prm.unit[ui];
        nxt = __shfl_sync(0xffffffffu, (uint32_t)prm.unit[ui + 1], 0);
        defer = left > 1 && (!(nxt & 0x8000u) || (cur & 0xC000u) == 0x4000u);
      };
      const bool out = code & 0x8000u;
      uint32_t rel = 0;
      auto retire = [&]() {
        wgmma_wait<0>();
        fence_regs(acc[0]);
        fence_regs(acc[1]);
        mbar_arrive1_if(rel, rel);
        rel = 0;
      };
      auto turn = [&](int accum, auto mode, auto tb, auto first) {
        bar_sync(1 + wg, 256);
        if (!first.value) retire();
        wgmma_fence();
        issue_slab(da, db, accum, mode, tb);
      };
      auto take_turn = [&](int accum, auto mode, auto first) {
        if (out) turn(accum, mode, IntC<1>{}, first);
        else turn(accum, mode, IntC<0>{}, first);
      };
      Fin f;
      int k = 0;
      const bool staged = pend == 2;
      if (out ? pend == 1 : !staged) {
        uint32_t redo = 0;
        static_for<0, 9>([&](auto kc) {
          constexpr int k = kc.value;
          take_turn(k > 0, IntC<k == 1 ? 2 : 0>{}, BoolC<k == 0>{});
          if (k == 1) {
            wgmma_fence();
            issue_colsum(f);
            bar_arrive(2 - wg, 256);
            pin_order(never, 62);
          }
          if (k >= 4) keep_alive(w_cut(k - 4), w_cut(k - 3), 62 + 2 * k);
          constexpr int p0 = x_pos(0, k), p1 = x_pos(0, k + 1), o0 = x_off(0, k), o1 = x_off(0, k + 1);
          const uint32_t rw = empty0 + 8 * ring_slot(it + o0 + (p0 == 0));
          const uint32_t rx = empty0 + 8 * (p0 == 0 ? ring_slot(it + o0 + 2 * wg) : NSLOT + 4 * wg + p0 - 1);
          const uint32_t wi = it + o1 + (p1 == 0), xi = it + o1 + 2 * wg;
          const uint32_t xbar = full0 + 8 * (p1 == 0 ? ring_slot(xi) : NSLOT + 4 * wg + p1 - 1);
          const uint32_t xpar = (p1 == 0 ? ring_round(xi) : pph >> (p1 == 0 ? 0 : p1 - 1)) & 1;
          if constexpr (p1 != 0) pph ^= 1u << (p1 - 1);
          uint32_t okp = probe(wi) & test(xbar, xpar);
          if (k == 2) okp &= test(ok_bar, uph ^ (pend != 0));
          rel = pick(tq == 0, rw, pick(tq < 3 && (k < 6 || out), rx, 0));
          if (k == 1) rel = pick(tq - 3 < 2u && pend == 1, empty0 + 8 * (NSLOT + 4 * wg + 3), rel);
          if (k == 1) step_finite(f);
          if (k == 2) {
            step_check(f, pend == 1);
            f.dst = o_base(prev) + warp * 3584 + lane * 4;
          }
          if (k == 7) redo = read_verdict();
          if (pend == 1) {
            if (k == 0) step_sums();
            if (k >= 3) step_write(f, w_cut(k - 3), w_cut(k - 2));
          }
          if (k == 8) {
            if (__any_sync(0xffffffffu, redo)) step_redo(prev);
            __syncwarp();
            mbar_arrive1_if(sfull0 + 8 * (2 * lane + wg), lane < 2 && pend);
          }
          const bool ok = __all_sync(0xffffffffu, okp);
          da = slot_desc(wi);
          db = p1 == 0 ? slot_desc(xi) : dq + (p1 - 1) * (PANEL >> 4);
          if (!ok) {
            retire();
            wait_full(wi);
            mbar_wait_warp(xbar, xpar);
            if (k == 2) mbar_wait_warp(ok_bar, uph ^ (pend != 0));
          }
        });
        k = 9;
      }
      const int nslab = unit_slabs(code);
      const bool part_in = unit_partial_in(code), part_out = unit_partial_out(code);
      uint32_t pos = k ? 4 : 0, wi = it + (k ? 13 : 1), xbar = full0 + 8 * (k ? NSLOT + 4 * wg + 3 : ring_slot(it + 2 * wg));
      auto part = [&]() { return g_part + (size_t)((((code >> 8) & 127) * 2 + rank) * 2 + wg) * (28 * 128) + tq; };
      auto load_part = [&](int t) {
#pragma unroll
        for (int i = 0; i < 14; i++) {
          const float4 v = __ldcg(part() + (t * 14 + i) * 128);
          s[4 * i] = v.x, s[4 * i + 1] = v.y, s[4 * i + 2] = v.z, s[4 * i + 3] = v.w;
        }
      };
      if (k < nslab - 1) {
        uint32_t r = it + (k ? 14 : 3);
        const uint32_t pat = staged ? kPat1 : kPat0, jobs = staged ? 3 : part_in ? 0x49 : 0;
        const uint32_t keep_pos = out ? (part_out ? 5 : 3) : 1;
        const int keep_k = nslab == 8 ? 4 : nslab - 5;
#pragma unroll 1
        do {
          take_turn(k > 0, IntC<0>{}, BoolC<false>{});
          rel = pick(tq == 0, empty0 + 8 * ring_slot(wi), pick(tq < 3 && (pos < keep_pos || k < keep_k), xbar + 8 * NBAR, 0));
          pos = next_pos(pos, k, pat);
          const bool ring = pos == 0;
          const uint32_t i = r + 2 * wg, q = pos - 1;
          wi = ring ? r + 1 : r;
          xbar = full0 + 8 * (ring ? ring_slot(i) : NSLOT + 4 * wg + q);
          const uint32_t xpar = (ring ? ring_round(i) : pph >> q) & 1;
          da = slot_desc(wi);
          db = ring ? slot_desc(i) : dq + q * (PANEL >> 4);
          pph ^= ring ? 0u : 1u << q;
          r += ring ? 3 : 1;
          const bool job = k < 7 && (jobs >> k & 1);
          if (job || !__all_sync(0xffffffffu, probe(wi) & test(xbar, xpar))) {
            if (job && staged) {
              if (k == 0) {
                mbar_wait_warp(ok_bar, uph ^ 1);
                store_half<0>(st_p, s);
              } else {
                store_half<1>(st_p, s);
              }
              step_signal(k);
            } else {
              retire();
              if (job) {
                if (k == 0) {
                  load_part(0);
                } else if (k == 3) {
#pragma unroll
                  for (int i2 = 0; i2 < 56; i2++) acc[0][i2] += s[i2];
                  load_part(1);
                } else {
#pragma unroll
                  for (int i2 = 0; i2 < 56; i2++) acc[1][i2] += s[i2];
                }
              }
            }
            wait_full(wi);
            mbar_wait_warp(xbar, xpar);
          }
        } while (++k < nslab - 1);
      }
      if (!out) {
        it += staged ? x_off(1, 10) : x_off(0, 10);
        turn(1, IntC<1>{}, IntC<0>{}, BoolC<false>{});
        keep_alive(w_cut(5), w_cut(6), 80);
        {
          const bool ok = __all_sync(0xffffffffu, probe(it));
          const uint32_t rw = empty0 + 8 * ring_slot(it - 1);
          da = slot_desc(it);
          wgmma_wait<1>();
          fence_regs(acc[0]);
          q_half<0>(st_q, s, acc[0], never);
          wgmma_wait<0>();
          fence_regs(acc[1]);
          q_half<1>(st_q, s, acc[1], never);
          mbar_arrive1_if(rw, tq == 0);
          if (!ok) wait_full(it);
        }
        fence_async_smem();
        float l[28];
        auto issue_s = [&](uint32_t dk, int accum) {
          wgmma_fence();
#pragma unroll
          for (int kk = 0; kk < 8; kk++)
            wgmma_n112<0>(s, dk + (kk >> 2) * 512 + (kk & 3) * 2, dq + (kk >> 2) * (PANEL >> 4) + (kk & 3) * 2, kk > 0 ? 1 : accum);
          wgmma_commit();
        };
        auto add_sums = [&]() {
#pragma unroll
          for (int jj = 0; jj < 14; jj++)
            asm volatile("{\n.reg .b32 t;\nshl.b32 t, %2, 16;\nadd.f32 %0, %0, t;\nand.b32 t, %2, 0xffff0000;\nadd.f32 %1, %1, t;\n}"
                         : "+f"(l[2 * jj]), "+f"(l[2 * jj + 1])
                         : "r"(ps[jj]));
        };
        auto softmax = [&](uint32_t par, int pin0) {
          const uint32_t pa = st_p + par * PANEL;
#pragma unroll
          for (int i = 0; i < 8 + SM_OFF; i++) s[i] = ex2(s[i]);
#pragma unroll
          for (int jj = 0; jj < 7; jj++) {
            const float* e = s + 8 * jj;
#pragma unroll
            for (int i = 8 * jj + 8 + SM_OFF; i < 8 * jj + 16 + SM_OFF; i++)
              if (i < 56) s[i] = ex2(s[i]);
            const uint32_t p0 = pack_bf16(e[0], e[1]), p1 = pack_bf16(e[2], e[3]), p2 = pack_bf16(e[4], e[5]), p3 = pack_bf16(e[6], e[7]);
            stsm_x4_t_pin(pa + jj * 2048, p0, p1, p2, p3, never, pin0);
            asm("add.rn.bf16x2 %0, %1, %2;" : "=r"(ps[2 * jj]) : "r"(p0), "r"(p1));
            asm("add.rn.bf16x2 %0, %1, %2;" : "=r"(ps[2 * jj + 1]) : "r"(p2), "r"(p3));
          }
        };
        bar_sync(1 + wg, 256);
        issue_s(da, never);
        bar_arrive(2 - wg, 256);
        {
#pragma unroll
          for (int i = 0; i < 28; i++) asm volatile("mov.b32 %0, 0;" : "=f"(l[i]));
          peek();
          const bool ok = __all_sync(0xffffffffu, probe(it + 1));
          wgmma_wait<0>();
          fence_regs(s);
          release(it);
          softmax(0, 176);
          if (!ok) wait_full(it + 1);
        }
        it += 1;
#pragma unroll 1
        for (int j = 1; j < 16; j++) {
          fence_async_smem();
          bar_sync(1 + wg, 256);
          issue_s(slot_desc(it), 0);
          pin_order(never, 2 * j + 128);
          const uint32_t okv = mbar_test(full0 + 8 * ring_slot(it + 1), ring_par(it + 1));
          const uint32_t nk = it + 2, ok = probe(nk);
          add_sums();
          if (!__all_sync(0xffffffffu, okv)) wait_full(it + 1);
          {
            const uint32_t dv = slot_desc(it + 1), dp = dq + (3 - (j & 1)) * (PANEL >> 4);
            wgmma_fence();
#pragma unroll
            for (int kk = 0; kk < 4; kk++) {
              wgmma_n112<1>(acc[0], dv + kk * 128, dp + kk * 2, kk > 0 ? 1 : j > 1);
              wgmma_n112<1>(acc[1], dv + 512 + kk * 128, dp + kk * 2, kk > 0 ? 1 : j > 1);
            }
          }
          wgmma_commit();
          bar_arrive(2 - wg, 256);
          wgmma_wait<1>();
          fence_regs(s);
          release(it);
          softmax(j & 1, 2 * j + 192);
          if (!__all_sync(0xffffffffu, ok)) {
            wait_full(nk);
          }
          wgmma_wait<0>();
          fence_regs(acc[0]);
          fence_regs(acc[1]);
          release(it + 1);
          it += 2;
        }
        it += 1;
        fence_async_smem();
        bar_sync(1 + wg, 256);
        wgmma_fence();
        issue_slab(slot_desc(it - 1), dq + 3 * (PANEL >> 4), 1, IntC<1>{}, IntC<0>{});
        pin_order(never, 182);
        mbar_arrive1_if(empty0 + 8 * (NSLOT + 4 * wg + (tq >> 1)), tq < 6);
        const uint32_t rv = empty0 + 8 * ring_slot(it - 1);
        next_unit(defer);
#pragma unroll
        for (int g = 0; g < 14; g++) asm volatile("add.rn.bf16x2 %0, %0, %1;" : "+r"(ps[g]) : "r"(pack_bf16(l[2 * g], l[2 * g + 1])));
        wgmma_wait_pin<1>(never, 170);
        fence_regs(acc[0]);
        pack_half<0>(s, acc[0], 1.f);
        fence_half<0>(s);
        wgmma_wait_pin<0>(never, 172);
        fence_regs(acc[1]);
        mbar_arrive1_if(rv, tq == 0);
        pack_half<1>(s, acc[1], 1.f);
        pend = 1;
      } else {
        turn(1, IntC<1>{}, IntC<1>{}, BoolC<false>{});
        pin_order(never, 186);
        it += nslab + 2 * (2 + (nslab - 6) / 5);
        peek();
        next_unit(defer);
        wgmma_wait<1>();
        fence_regs(acc[0]);
        pack_half<0>(s, acc[0], 1.f);
        fence_half<0>(s);
        wgmma_wait_pin<0>(never, 174);
        fence_regs(acc[1]);
        mbar_arrive1_if(xbar + 8 * NBAR, tq < 2 && (pos < 3 || part_out));
        release(wi);
        pack_half<1>(s, acc[1], 1.f);
        pend = 2;
        if (part_out) {
#pragma unroll
          for (int i = 0; i < 28; i++) {
            const float* a = &acc[i / 14][(i % 14) * 4];
            __stcg(part() + i * 128, make_float4(a[0], a[1], a[2], a[3]));
          }
          pend = 3;
        }
      }
      if (!defer) {
        mbar_wait_warp(ok_bar, uph);
        bar_sync(3 + wg, 128);
        if (pend == 1) {
          step_sums();
          bar_sync(3 + wg, 128);
          wgmma_fence();
          issue_colsum(f);
          step_finite(f);
          wgmma_wait<0>();
          free_panel(3);
          step_check(f, true);
          bar_sync(3 + wg, 128);
          if (__any_sync(0xffffffffu, read_verdict())) {
            step_redo(code);
          } else {
            f.dst = o_base(code) + warp * 3584 + lane * 4;
            step_write(f, 0, 56);
          }
        } else if (pend == 2) {
          store_half<0>(st_p, s);
          store_half<1>(st_p, s);
        }
        step_signal(0);
        mbar_arrive1_if(sfull0 + 8 * (2 + wg), lane == 0);
        pend = 0;
#pragma unroll
        for (int i = 0; i < 14; i++) ps[i] = 0;
        if (left > 1) {
          wait_full(it + 1);
          wait_full(it + 2 * wg);
        }
      }
      prev = code, code = nxt, uph ^= 1;
    }
    if (wg == 0) bar_sync(1, 256);
  }
}

typedef CUresult (*EncodeFn)(CUtensorMap*, CUtensorMapDataType, cuuint32_t, void*, const cuuint64_t*, const cuuint64_t*,
                             const cuuint32_t*, const cuuint32_t*, CUtensorMapInterleave, CUtensorMapSwizzle,
                             CUtensorMapL2promotion, CUtensorMapFloatOOBfill);

bool encode(EncodeFn fn, CUtensorMap* m, const void* ptr, int rank, const cuuint64_t* dims, const cuuint64_t* strides,
            const cuuint32_t* box, CUtensorMapL2promotion promo, CUtensorMapSwizzle swz = CU_TENSOR_MAP_SWIZZLE_128B) {
  const cuuint32_t es[3] = {1, 1, 1};
  return fn(m, CU_TENSOR_MAP_DATA_TYPE_BFLOAT16, rank, const_cast<void*>(ptr), dims, strides, box, es,
            CU_TENSOR_MAP_INTERLEAVE_NONE, swz, promo,
            CU_TENSOR_MAP_FLOAT_OOB_FILL_NONE) == CUDA_SUCCESS;
}
bool encode_panels(EncodeFn fn, CUtensorMap* m, const void* ptr, uint64_t rows, uint64_t cols, uint32_t box_rows,
                   uint32_t box_blocks = 2) {
  const cuuint64_t dims[3] = {64, rows, cols / 64};
  const cuuint64_t strides[2] = {cols * 2, 128};
  const cuuint32_t box[3] = {64, box_rows, box_blocks};
  CUtensorMapL2promotion promo = CU_TENSOR_MAP_L2_PROMOTION_L2_128B;
  return encode(fn, m, ptr, 3, dims, strides, box, promo);
}
bool encode_2d(EncodeFn fn, CUtensorMap* m, const void* ptr, uint64_t rows, uint64_t cols, uint32_t box_rows,
               CUtensorMapSwizzle swz = CU_TENSOR_MAP_SWIZZLE_128B) {
  const cuuint64_t dims[2] = {cols, rows};
  const cuuint64_t strides[1] = {cols * 2};
  const cuuint32_t box[2] = {64, box_rows};
  CUtensorMapL2promotion promo = CU_TENSOR_MAP_L2_PROMOTION_L2_128B;
  return encode(fn, m, ptr, 2, dims, strides, box, promo, swz);
}

constexpr int kTunedPairs = 66;
const uint16_t kTunedBlock[kAttnUnits] = {
    20480, 20484, 20488, 16396, 16400, 16404, 16408, 16412, 16416, 16420, 16424, 16428, 16432, 16436, 16440, 16444,
    20481, 20485, 20489, 16397, 16401, 16405, 16409, 16413, 16417, 16421, 16425, 16429, 16433, 16437, 16441, 16445,
    20482, 20486, 20490, 16398, 16402, 16406, 16410, 16414, 16418, 16422, 16426, 16430, 16434, 16438, 16442, 16446,
    20483, 20487, 20491, 16399, 16403, 16407, 16411, 16415, 16419, 16423, 16427, 16431, 16435, 16439, 16443, 16447,
    16448, 16450, 16452, 16454, 16456, 16458, 16460, 16462, 16464, 16466, 16468, 16470, 20992, 20994, 20996, 20998,
    16449, 16451, 16453, 16455, 16457, 16459, 16461, 16463, 16465, 16467, 16469, 16471, 20993, 20995, 20997, 20999,
    21000, 16908, 16912, 16916, 16920, 16924, 16928, 16932, 16936, 16940, 16944, 16948, 16952, 16956, 16960, 16964,
    21001, 16909, 16913, 16917, 16921, 16925, 16929, 16933, 16937, 16941, 16945, 16949, 16953, 16957, 16961, 16965,
    21002, 16910, 16914, 16918, 16922, 16926, 16930, 16934, 16938, 16942, 16946, 16950, 16954, 16958, 16962, 16966,
    21003, 16911, 16915, 16919, 16923, 16927, 16931, 16935, 16939, 16943, 16947, 16951, 16955, 16959, 16963, 16967,
    16968, 16970, 16972, 16974, 16976, 16978, 16980, 16982, 21504, 21506, 21508, 21510, 21512, 21514, 17420, 17422,
    16969, 16971, 16973, 16975, 16977, 16979, 16981, 16983, 21505, 21507, 21509, 21511, 21513, 21515, 17421, 17423,
    17424, 17428, 17432, 17436, 17440, 17444, 17448, 17452, 17456, 17460, 17464, 17468, 17472, 17476, 17480, 17484,
    17425, 17429, 17433, 17437, 17441, 17445, 17449, 17453, 17457, 17461, 17465, 17469, 17473, 17477, 17481, 17485,
    17426, 17430, 17434, 17438, 17442, 17446, 17450, 17454, 17458, 17462, 17466, 17470, 17474, 17478, 17482, 17486,
    17427, 17431, 17435, 17439, 17443, 17447, 17451, 17455, 17459, 17463, 17467, 17471, 17475, 17479, 17483, 17487,
    17488, 17490, 17492, 17494, 22016, 22018, 22020, 22022, 22024, 22026, 17932, 17934, 17936, 17938, 17940, 17942,
    17489, 17491, 17493, 17495, 22017, 22019, 22021, 22023, 22025, 22027, 17933, 17935, 17937, 17939, 17941, 17943,
    17944, 17947, 17950, 17953, 17956, 17959, 17962, 17965, 17968, 17971, 17974, 17977, 17980, 17983, 17986, 17989,
    17945, 17948, 17951, 17954, 17957, 17960, 17963, 17966, 17969, 17972, 17975, 17978, 17981, 17984, 17987, 17990,
    17946, 17949, 17952, 17955, 17958, 17961, 17964, 17967, 17970, 17973, 17976, 17979, 17982, 17985, 17988, 17991,
    17992, 18003, 22534, 4189, 4200, 4211, 4222, 4233, 4244, 4255, 4266, 4277, 4288, 4299, 4310, 4321,
    17993, 18004, 22535, 4190, 4201, 4212, 4223, 4234, 4245, 4256, 4267, 4278, 4289, 4300, 4311, 4322,
    17994, 18005, 22536, 4191, 4202, 4213, 4224, 4235, 4246, 4257, 4268, 4279, 4290, 4301, 4312, 4323,
    17995, 18006, 22537, 4192, 4203, 4214, 4225, 4236, 4247, 4258, 4269, 4280, 4291, 4302, 4313, 4324,
    17996, 18007, 22538, 4193, 4204, 4215, 4226, 4237, 4248, 4259, 4270, 4281, 4292, 4303, 4314, 4325,
    17997, 22528, 22539, 4194, 4205, 4216, 4227, 4238, 4249, 4260, 4271, 4282, 4293, 4304, 4315, 4326,
    17998, 22529, 4184, 4195, 4206, 4217, 4228, 4239, 4250, 4261, 4272, 4283, 4294, 4305, 4316, 4327,
    17999, 22530, 4185, 4196, 4207, 4218, 4229, 4240, 4251, 4262, 4273, 4284, 4295, 4306, 4317, 4328,
    18000, 22531, 4186, 4197, 4208, 4219, 4230, 4241, 4252, 4263, 4274, 4285, 4296, 4307, 4318, 4329,
    18001, 22532, 4187, 4198, 4209, 4220, 4231, 4242, 4253, 4264, 4275, 4286, 4297, 4308, 4319, 4330,
    18002, 22533, 4188, 4199, 4210, 4221, 4232, 4243, 4254, 4265, 4276, 4287, 4298, 4309, 4320, 4331};
const uint8_t kTunedLen[kTunedPairs] = {
    9, 9, 9, 9, 9, 9, 9, 9, 9, 9, 9, 9, 9, 9, 9, 9, 9, 9, 9, 9, 9, 9, 9, 9, 9, 8, 9, 9, 9, 9, 9, 9, 9,
    9, 9, 9, 9, 9, 9, 9, 9, 9, 9, 9, 9, 9, 9, 9, 9, 9, 8, 9, 9, 9, 9, 9, 9, 9, 9, 9, 9, 9, 9, 9, 9, 9};
const uint8_t kTunedDelay[kTunedPairs] = {
    0, 29, 5, 0, 0, 0, 3, 0, 0, 11, 1, 0, 0, 0, 13, 27, 0, 113, 0, 0, 0, 0,
    62, 0, 54, 27, 0, 0, 0, 9, 0, 107, 0, 1, 64, 1, 0, 3, 0, 101, 0, 15, 0, 0,
    60, 9, 62, 0, 0, 0, 0, 0, 0, 0, 0, 0, 0, 1, 3, 11, 0, 89, 7, 9, 54, 58};
const uint16_t kTunedUnit[] = {
    0, 32783, 184, 218, 290, 369, 470, 380, 447, 45, 16515, 37391, 233, 289, 464, 390, 475, 367,
    58, 145, 38159, 248, 288, 416, 342, 427, 478, 19, 84, 135, 173, 16604, 46351, 451, 16856, 59407,
    54, 91, 107, 209, 16622, 48143, 388, 16793, 61711, 2, 66, 37903, 232, 287, 400, 501, 411, 462,
    42, 129, 158, 227, 272, 16710, 49679, 410, 429, 48, 34063, 181, 200, 286, 384, 485, 395, 494,
    52, 87, 105, 192, 237, 16676, 49423, 16889, 64527, 28, 35855, 182, 201, 304, 432, 358, 443, 510,
    41, 128, 16541, 41999, 267, 319, 389, 474, 366, 39, 77, 155, 16578, 44303, 316, 420, 16825, 62735,
    34, 67, 150, 16571, 43023, 299, 403, 424, 365, 22, 90, 16522, 39951, 280, 300, 372, 16777, 61455,
    44, 36111, 166, 216, 271, 496, 422, 507, 399, 13, 115, 176, 197, 275, 328, 450, 471, 508,
    16, 33039, 169, 234, 306, 385, 486, 396, 463, 80, 118, 168, 202, 321, 353, 454, 364, 431,
    40, 79, 156, 242, 255, 16694, 50447, 16746, 64015, 35, 69, 151, 189, 16620, 45583, 467, 16872, 59663,
    7, 76, 123, 225, 254, 309, 16881, 52239, 349, 18, 82, 134, 171, 16619, 45071, 387, 16792, 58383,
    15, 101, 179, 230, 263, 318, 341, 426, 445, 17, 33295, 185, 250, 322, 401, 502, 412, 479,
    14, 100, 177, 229, 261, 314, 355, 16760, 57359, 29, 35343, 38927, 260, 297, 466, 16871, 53775, 20,
    86, 136, 175, 221, 323, 16833, 51215, 55823, 8, 78, 124, 226, 239, 294, 354, 407, 476, 3,
    68, 119, 188, 16588, 46095, 435, 16840, 57871, 43, 114, 127, 196, 273, 295, 16754, 52495, 461, 49,
    34831, 170, 203, 291, 417, 343, 428, 495, 64, 102, 183, 249, 305, 337, 438, 348, 415, 32,
    33807, 165, 247, 270, 480, 406, 491, 383, 57, 144, 16494, 42255, 283, 317, 468, 16873, 63759, 31,
    117, 164, 246, 279, 330, 371, 16776, 56591, 25, 112, 141, 195, 256, 311, 16770, 51727, 477, 23,
    92, 139, 241, 16591, 48399, 404, 16809, 62479, 10, 97, 16510, 41487, 268, 336, 421, 506, 398, 6,
    74, 16506, 39183, 264, 334, 357, 442, 493, 63, 149, 167, 217, 320, 448, 374, 459, 351, 21,
    88, 137, 224, 206, 324, 465, 375, 460, 60, 99, 160, 244, 259, 312, 434, 16839, 54543, 36,
    71, 152, 16575, 43279, 315, 340, 16745, 60687, 24, 94, 16524, 39439, 281, 332, 436, 16841, 61967, 46,
    132, 178, 198, 262, 333, 484, 378, 397, 59, 130, 143, 212, 258, 296, 418, 439, 492, 62,
    148, 163, 214, 278, 298, 339, 16744, 56335, 53, 89, 106, 16577, 44047, 331, 356, 16761, 59919, 1,
    65, 36879, 199, 284, 335, 405, 490, 350, 5, 72, 121, 208, 253, 16692, 50191, 16730, 64783, 56,
    95, 16493, 40975, 16650, 49167, 53263, 382, 4, 70, 120, 190, 16589, 47375, 499, 345, 381, 55, 93,
    108, 210, 223, 325, 338, 16775, 53519, 50, 83, 103, 172, 16635, 45327, 419, 16824, 58639, 38, 75,
    16538, 40207, 265, 303, 373, 458, 509, 33, 81, 37135, 215, 269, 368, 469, 379, 446, 37, 73,
    153, 240, 222, 293, 16865, 51471, 57615, 9, 96, 16509, 41231, 282, 301, 452, 16857, 63503, 26, 113,
    142, 16595, 43535, 302, 500, 394, 413, 12, 146, 159, 228, 274, 327, 402, 16807, 54287, 51, 85,
    104, 174, 16636, 47119, 483, 16888, 60431, 47, 133, 180, 231, 285, 352, 453, 363, 430, 11, 35087,
    186, 219, 307, 433, 359, 444, 511, 27, 98, 111, 243, 16641, 47631, 437, 347, 414, 61, 147,
    161, 213, 276, 313, 482, 16887, 55311, 30, 116, 162, 245, 277, 329, 498, 16728, 55567};
void build_schedule(Params& prm, int pairs) {
  for (int i = 0; i < kAttnUnits; i++) prm.blk[i] = (uint16_t)(i | 1 << 12);
  uint8_t delay[kMaxPairs] = {};
  static uint16_t lists[kMaxPairs][kMaxUnits];
  int n[kMaxPairs] = {};
  double t[kMaxPairs] = {};
  const double ta = 40.0, to = 59.0;
  for (int u = 0; u < kUnits; u++) {
    int p = 0;
    for (int q = 1; q < pairs; q++)
      if (t[q] < t[p] - 1e-9) p = q;
    uint16_t code;
    if (u < kAttnUnits) {
      code = (uint16_t)u;
    } else {
      const int o = u - kAttnUnits, g2 = o / 5, r = o % 5;
      code = (uint16_t)(0x800F | (r < 4 ? ((2 * g2 + (r >> 1)) << 2) | (r & 1) : ((2 * g2) << 2) | 2) << 8);
    }
    lists[p][n[p]++] = code;
    t[p] += u < kAttnUnits ? ta : to;
  }
  if (pairs == kTunedPairs) {
    for (int p = 0, o = 0; p < pairs; p++) {
      n[p] = kTunedLen[p];
      delay[p] = kTunedDelay[p];
      for (int i = 0; i < n[p]; i++) lists[p][i] = kTunedUnit[o++];
    }
    for (int i = 0; i < kAttnUnits; i++) prm.blk[i] = kTunedBlock[i];
  }
  int o = 0;
  for (int p = 0; p < pairs; p++) {
    prm.head[p] = o | n[p] << 10 | delay[p] << 15 | (uint32_t)(lists[p][0] & 511) << 23;
    for (int i = 0; i < n[p]; i++) prm.unit[o++] = lists[p][i];
  }
}

}

extern "C" void kernel_launch(void* const* d_in, const int* in_sizes, int n_in, void* d_out, int out_size) {
  (void)in_sizes; (void)n_in; (void)out_size;
  void* fnp = nullptr;
  cudaDriverEntryPointQueryResult qr;
  if (cudaGetDriverEntryPoint("cuTensorMapEncodeTiled", &fnp, cudaEnableDefault, &qr) != cudaSuccess || !fnp) return;
  EncodeFn fn = (EncodeFn)fnp;
  void* optr = nullptr;
  cudaGetSymbolAddress(&optr, g_o);
  Params prm;
  bool ok = true;
  for (int br = 0; br < 2; br++) {
    void* const* in = d_in + 5 * br;
    ok &= encode_2d(fn, &prm.x[br], in[0], (uint64_t)kB * kSq, kD, NQ);
    ok &= encode_panels(fn, &prm.k[br], in[1], (uint64_t)kB * kH * kSk, kDh, 64);
    ok &= encode_panels(fn, &prm.v[br], in[2], (uint64_t)kB * kH * kSk, kDh, 64);
    ok &= encode_panels(fn, &prm.wq[br], in[3], kD, kH * kDh, 64);
    ok &= encode_panels(fn, &prm.wo[br], in[4], kH * kDh, kD, 64);
    prm.xp[br] = (const __nv_bfloat16*)in[0];
    prm.wp[br] = (const __nv_bfloat16*)in[3];
    prm.kp[br] = (const __nv_bfloat16*)in[1];
    prm.vp[br] = (const __nv_bfloat16*)in[2];
  }
  ok &= encode_2d(fn, &prm.o_ld, optr, (uint64_t)kAttnUnits * 4 * kSq, 64, NQ, CU_TENSOR_MAP_SWIZZLE_NONE);
  ok &= encode_panels(fn, &prm.out, d_out, (uint64_t)kB * kSq, 2 * kD, ST_ROWS, 1);
  if (!ok) return;
  cudaFuncSetAttribute(mha_fused_kernel, cudaFuncAttributeMaxDynamicSharedMemorySize, SMEM_BYTES);
  cudaLaunchConfig_t cfg = {};
  cfg.gridDim = dim3(2);
  cfg.blockDim = dim3(384);
  cfg.dynamicSmemBytes = SMEM_BYTES;
  cfg.stream = cudaStreamPerThread;
  int pairs = 0;
  if (cudaOccupancyMaxActiveClusters(&pairs, mha_fused_kernel, &cfg) != cudaSuccess || pairs < 1) return;
  if (pairs > kMaxPairs) pairs = kMaxPairs;
  if (pairs < 24) return;
  build_schedule(prm, pairs);
  mha_fused_kernel<<<2 * pairs, 384, SMEM_BYTES, cudaStreamPerThread>>>(prm);
}
```

```cpp
#include <cuda_runtime.h>
#include <cuda_bf16.h>
#include <cuda.h>
#include <stdint.h>

namespace {

constexpr int kB = 16, kSq = 224, kD = 640, kH = 32, kSk = 1024, kDh = 128;
constexpr int kGroups = 2 * kB;
constexpr int kAttnUnits = kGroups * kH / 2;
constexpr int kOutUnits = kGroups * 5 / 2;
constexpr int kUnits = kAttnUnits + kOutUnits;
constexpr int kMaxUnits = kUnits + 64;
constexpr int kMaxPairs = 72;
constexpr int NQ = 112;
constexpr int PANEL = NQ * 128;
constexpr float kQScale = 0.08838834764831845f * 1.4426950408889634f;
constexpr int SLOT = 16384;
constexpr int NSLOT = 7;

constexpr int SM_PANEL = 0;
constexpr int SM_RING = SM_PANEL + 8 * PANEL;
constexpr int NBAR = NSLOT + 8;
constexpr int SM_RCP = SM_RING + NSLOT * SLOT;
constexpr int SM_BAR = SM_RCP + 640;
constexpr int SM_END = SM_BAR + 8 * (2 * NBAR + 12) + 32;
constexpr int SMEM_BYTES = SM_END + 1024;
static_assert(SM_RING % 1024 == 0 && PANEL % 1024 == 0, "swizzle alignment");
static_assert(SMEM_BYTES <= 232448, "smem");

struct Params {
  CUtensorMap x[2], wq[2], kv[4], wo[2];
  CUtensorMap o_ld, out;
  const __nv_bfloat16* xp[2];
  const __nv_bfloat16* wp[2];
  const __nv_bfloat16* kp[2];
  const __nv_bfloat16* vp[2];
  __nv_bfloat16* op;
  uint32_t head[kMaxPairs];
  uint16_t unit[kMaxUnits];
  uint16_t blk[kAttnUnits];
};

struct Unit {
  bool attn, mc;
  int g, hc;
  int h0, nslab;
};
__device__ __forceinline__ int unit_slabs(uint32_t u) {
  return (u & 0x8000u) ? 4 * ((u & 15) + 1 - ((u >> 4) & 15)) : kD / 64;
}
__device__ __forceinline__ Unit decode_unit(uint32_t u, uint32_t rank) {
  Unit r;
  r.attn = !(u & 0x8000u);
  r.nslab = unit_slabs(u);
  if (r.attn) {
    r.g = (u >> 4) & 31;
    r.hc = (u & 15) * 2 + rank;
    r.mc = true;
    r.h0 = 0;
  } else {
    const uint32_t t = (u >> 8) & 3;
    r.mc = t < 2;
    r.g = ((u >> 10) & 31) + (t < 2 ? 0 : rank);
    r.hc = t < 2 ? 2 * t + rank : 4;
    r.h0 = (u >> 4) & 15;
  }
  return r;
}

__device__ uint4 g_qrow[2 * kMaxPairs * 2 * 16 * 128];
__device__ unsigned int g_pc[128 * 16 * 2];
__device__ __nv_bfloat16 g_o[(size_t)kAttnUnits * kSq * 2 * kDh];
__device__ unsigned int g_ticket;
__device__ unsigned int g_rd[kAttnUnits];
__device__ unsigned int g_cnt[kAttnUnits];

constexpr int CREGS = 232, SM_OFF = -2, Q_PIN = 0x15, ST_ROWS = 56;
template <bool V>
struct BoolC {
  static constexpr bool value = V;
};
template <int V>
struct IntC {
  static constexpr int value = V;
};
template <int I, int N, class F>
__device__ __forceinline__ void static_for(F&& f) {
  if constexpr (I < N) {
    f(IntC<I>{});
    static_for<I + 1, N>(f);
  }
}
constexpr uint32_t kPat0 = 04321432100, kPat1 = 04302102100;
__host__ __device__ constexpr int x_pos(int pat, int k) { return ((pat == 0 ? kPat0 : kPat1) >> 3 * k) & 7; }
__host__ __device__ constexpr int x_off(int pat, int k) { return k == 0 ? 0 : x_off(pat, k - 1) + (x_pos(pat, k - 1) == 0 ? 3 : 1); }
__host__ __device__ constexpr int w_cut(int i) { return 56 * i / 5; }
__device__ __forceinline__ uint32_t unit_pattern(uint32_t u, uint32_t prev) {
  return !(u & 0x8000u) && (prev & 0x8000u) ? kPat1 : kPat0;
}
__device__ __forceinline__ uint32_t next_pos(uint32_t pos, int k, uint32_t pat) {
  return k < 9 ? (pat >> (3 * k + 3)) & 7 : pos == 4 ? 0 : pos + 1;
}
__device__ __forceinline__ uint32_t pick(bool c, uint32_t a, uint32_t b) {
  uint32_t r;
  asm("{\n.reg .pred p;\nsetp.ne.u32 p, %1, 0;\nselp.u32 %0, %2, %3, p;\n}" : "=r"(r) : "r"((uint32_t)c), "r"(a), "r"(b));
  return r;
}
__device__ __forceinline__ uint32_t ring_round(uint32_t i) { return (i * 9363u) >> 16; }
__device__ __forceinline__ uint32_t ring_slot(uint32_t i) { return i - NSLOT * ring_round(i); }
__device__ __forceinline__ uint32_t ring_par(uint32_t i) { return ring_round(i) & 1; }

__device__ __forceinline__ uint32_t smem_u32(const void* p) { return (uint32_t)__cvta_generic_to_shared(p); }
__device__ __forceinline__ void mbar_init(uint32_t bar, uint32_t cnt) {
  asm volatile("mbarrier.init.shared::cta.b64 [%0], %1;" ::"r"(bar), "r"(cnt));
}
__device__ __forceinline__ void mbar_arrive1_if(uint32_t bar, bool pred) {
  asm volatile("{\n.reg .pred p;\nsetp.ne.u32 p, %1, 0;\n@p mbarrier.arrive.shared::cta.b64 _, [%0];\n}" ::"r"(bar), "r"((uint32_t)pred)
               : "memory");
}
__device__ __forceinline__ void mbar_wait_warp(uint32_t bar, uint32_t parity) {
  asm volatile(
      "{\n.reg .pred p, q;\n.reg .u32 c;\n"
      "mov.u32 c, 0;\n"
      "SPIN:\n"
      "mbarrier.try_wait.parity.shared::cta.b64 p, [%0], %1;\n"
      "vote.sync.all.pred q, p, 0xffffffff;\n"
      "@q bra.uni DONE;\n"
      "add.u32 c, c, 1;\n"
      "setp.gt.u32 q, c, 0x1000000;\n"
      "@q trap;\n"
      "bra.uni SPIN;\n"
      "DONE:\n}" ::"r"(bar),
      "r"(parity)
      : "memory");
}
__device__ __forceinline__ uint32_t mbar_test(uint32_t bar, uint32_t parity) {
  uint32_t ok;
  asm volatile(
      "{\n.reg .pred p;\nmbarrier.test_wait.parity.shared::cta.b64 p, [%1], %2;\nselp.u32 %0, 1, 0, p;\n}"
      : "=r"(ok)
      : "r"(bar), "r"(parity)
      : "memory");
  return ok;
}
__device__ __forceinline__ uint32_t mbar_test_if(uint32_t bar, uint32_t parity, bool pred) {
  uint32_t ok;
  asm volatile(
      "{\n.reg .pred p, q;\nsetp.ne.u32 q, %3, 0;\nsetp.eq.u32 p, %3, 0;\n"
      "@q mbarrier.test_wait.parity.shared::cta.b64 p, [%1], %2;\nselp.u32 %0, 1, 0, p;\n}"
      : "=r"(ok)
      : "r"(bar), "r"(parity), "r"((uint32_t)pred)
      : "memory");
  return ok;
}
#define ELECTED "{\n.reg .pred e;\nelect.sync _|e, 0xffffffff;\n@e "
constexpr uint64_t kEvictFirst = 0x12F0000000000000ull, kEvictNormal = 0x1000000000000000ull;
__device__ __forceinline__ void flag_wait(const unsigned int* p, uint32_t target) {
  asm volatile(
      "{\n.reg .pred p, q;\n.reg .u32 c, v;\n"
      "mov.u32 c, 0;\n"
      "SPIN:\n"
      "ld.acquire.gpu.global.u32 v, [%0];\n"
      "setp.ge.u32 p, v, %1;\n"
      "vote.sync.all.pred q, p, 0xffffffff;\n"
      "@q bra.uni DONE;\n"
      "nanosleep.u32 200;\n"
      "add.u32 c, c, 1;\n"
      "setp.gt.u32 q, c, 0x1000000;\n"
      "@q trap;\n"
      "bra.uni SPIN;\n"
      "DONE:\n}" ::"l"(p),
      "r"(target)
      : "memory");
}
__device__ __forceinline__ uint32_t flags_wait(const unsigned int* p, uint32_t target, uint32_t need) {
  uint32_t m;
  asm volatile(
      "{\n.reg .pred p, q;\n.reg .u32 c, v;\n"
      "mov.u32 c, 0;\n"
      "SPIN:\n"
      "ld.acquire.gpu.global.u32 v, [%1];\n"
      "setp.ge.u32 p, v, %2;\n"
      "vote.sync.ballot.b32 %0, p, 0xffffffff;\n"
      "and.b32 v, %0, %3;\n"
      "setp.eq.u32 q, v, %3;\n"
      "@q bra.uni DONE;\n"
      "add.u32 c, c, 1;\n"
      "setp.gt.u32 q, c, 0x1000000;\n"
      "@q trap;\n"
      "bra.uni SPIN;\n"
      "DONE:\n"
      "fence.proxy.async.global;\n}"
      : "=&r"(m)
      : "l"(p), "r"(target), "r"(need)
      : "memory");
  return m;
}
__device__ __forceinline__ void e_arrive(uint32_t bar, uint32_t n) {
  asm volatile(ELECTED "mbarrier.arrive.shared::cta.b64 _, [%0], %1;\n}" ::"r"(bar), "r"(n) : "memory");
}
__device__ __forceinline__ void e_expect_tx(uint32_t bar, uint32_t bytes) {
  asm volatile(ELECTED "mbarrier.arrive.expect_tx.shared::cta.b64 _, [%0], %1;\n}" ::"r"(bar), "r"(bytes) : "memory");
}
__device__ __forceinline__ void tma_ld2(uint32_t dst, const CUtensorMap* m, int c0, int c1, uint32_t bar, uint64_t pol) {
  asm volatile(ELECTED
               "cp.async.bulk.tensor.2d.shared::cluster.global.mbarrier::complete_tx::bytes.L2::cache_hint [%0], [%1, {%3, %4}], "
               "[%2], %5;\n}" ::"r"(dst),
               "l"(m), "r"(bar), "r"(c0), "r"(c1), "l"(pol)
               : "memory");
}
__device__ __forceinline__ void tma_ld2_mc(uint32_t dst, const CUtensorMap* m, int c0, int c1, uint32_t bar, uint64_t pol) {
  asm volatile(ELECTED
               "cp.async.bulk.tensor.2d.shared::cluster.global.mbarrier::complete_tx::bytes.multicast::cluster.L2::cache_hint "
               "[%0], [%1, {%3, %4}], [%2], %5, %6;\n}" ::"r"(dst),
               "l"(m), "r"(bar), "r"(c0), "r"(c1), "h"((uint16_t)3), "l"(pol)
               : "memory");
}
__device__ __forceinline__ void tma_ld3(uint32_t dst, const CUtensorMap* m, int c1, int c2, uint32_t bar, uint64_t pol) {
  asm volatile(ELECTED
               "cp.async.bulk.tensor.3d.shared::cluster.global.mbarrier::complete_tx::bytes.L2::cache_hint [%0], [%1, {%3, %4, "
               "%5}], [%2], %6;\n}" ::"r"(dst),
               "l"(m), "r"(bar), "r"(0), "r"(c1), "r"(c2), "l"(pol)
               : "memory");
}
__device__ __forceinline__ void tma_st3(const CUtensorMap* m, int c1, int c2, uint32_t src, bool add) {
  if (add)
    asm volatile(ELECTED "cp.reduce.async.bulk.tensor.3d.global.shared::cta.add.bulk_group [%0, {%2, %3, %4}], [%1];\n}" ::"l"(m), "r"(src),
                 "r"(0), "r"(c1), "r"(c2)
                 : "memory");
  else
    asm volatile(ELECTED "cp.async.bulk.tensor.3d.global.shared::cta.bulk_group [%0, {%2, %3, %4}], [%1];\n}" ::"l"(m), "r"(src), "r"(0),
                 "r"(c1), "r"(c2)
                 : "memory");
}
__device__ __forceinline__ void wgmma_fence() { asm volatile("wgmma.fence.sync.aligned;" ::: "memory"); }
__device__ __forceinline__ void wgmma_commit() { asm volatile("wgmma.commit_group.sync.aligned;" ::: "memory"); }
template <int N>
__device__ __forceinline__ void wgmma_wait() {
  asm volatile("wgmma.wait_group.sync.aligned %0;" ::"n"(N) : "memory");
}
template <int N>
__device__ __forceinline__ void wgmma_wait_pin(int never, int c) {
  asm volatile("{\n.reg .pred p;\nsetp.eq.u32 p, %1, %2;\nAGAIN:\nwgmma.wait_group.sync.aligned %0;\n@p bra.uni AGAIN;\n}" ::"n"(N),
               "r"(never), "r"(c)
               : "memory");
}
__device__ __forceinline__ void pin_order(int never, int c) {
  asm volatile("{\n.reg .pred p;\nsetp.eq.u32 p, %0, %1;\nAGAIN:\n@p nanosleep.u32 1;\n@p bra.uni AGAIN;\n}" ::"r"(never), "r"(c) : "memory");
}
template <int N>
__device__ __forceinline__ void fence_regs(float (&d)[N]) {
#pragma unroll
  for (int i = 0; i < N; i++) asm volatile("" : "+f"(d[i])::"memory");
}
__device__ __forceinline__ void fence_async_smem() { asm volatile("fence.proxy.async.shared::cta;" ::: "memory"); }
__device__ __forceinline__ void bar_sync(int id, int n) { asm volatile("bar.sync %0, %1;" ::"r"(id), "r"(n) : "memory"); }
__device__ __forceinline__ void bar_arrive(int id, int n) {
  asm volatile("bar.arrive %0, %1;" ::"r"(id), "r"(n) : "memory");
}
__device__ __forceinline__ void stsm_x4_t(uint32_t addr, uint32_t r0, uint32_t r1, uint32_t r2, uint32_t r3) {
  asm volatile("stmatrix.sync.aligned.m8n8.x4.trans.shared.b16 [%0], {%1, %2, %3, %4};" ::"r"(addr), "r"(r0), "r"(r1),
               "r"(r2), "r"(r3)
               : "memory");
}
__device__ __forceinline__ void stsm_x4_t_pin(uint32_t addr, uint32_t r0, uint32_t r1, uint32_t r2, uint32_t r3, int never, int c) {
  asm volatile(
      "{\n.reg .pred p;\nsetp.eq.u32 p, %5, %6;\nAGAIN:\n"
      "stmatrix.sync.aligned.m8n8.x4.trans.shared.b16 [%0], {%1, %2, %3, %4};\n@p bra.uni AGAIN;\n}" ::"r"(addr),
      "r"(r0), "r"(r1), "r"(r2), "r"(r3), "r"(never), "r"(c)
      : "memory");
}
__device__ __forceinline__ uint32_t pack_bf16(float lo, float hi) {
  uint32_t r;
  asm("cvt.rn.bf16x2.f32 %0, %1, %2;" : "=r"(r) : "f"(hi), "f"(lo));
  return r;
}
__device__ __forceinline__ float ex2(float x) {
  float y;
  asm("ex2.approx.ftz.f32 %0, %1;" : "=f"(y) : "f"(x));
  return y;
}
__device__ __forceinline__ uint32_t mk_desc(uint32_t addr) { return (1u << 16) | ((addr & 0x3FFFFu) >> 4); }

template <int TA, int TB = 0>
__device__ __forceinline__ void wgmma_n112(float (&d)[56], uint32_t descA, uint32_t descB, int scaleD) {
  asm volatile(
      "{\n.reg .pred p;\n.reg .b32 hi, hb;\n.reg .b64 da, db;\nsetp.ne.b32 p, %58, 0;\n"
      "mov.b32 hi, 0x40000040;\nmov.b32 hb, %61;\nmov.b64 da, {%56, hi};\nmov.b64 db, {%57, hb};\n"
      "wgmma.mma_async.sync.aligned.m64n112k16.f32.bf16.bf16 "
      "{%0, %1, %2, %3, %4, %5, %6, %7, %8, %9, %10, %11, %12, %13, "
      "%14, %15, %16, %17, %18, %19, %20, %21, %22, %23, %24, %25, %26, %27, "
      "%28, %29, %30, %31, %32, %33, %34, %35, %36, %37, %38, %39, %40, %41, "
      "%42, %43, %44, %45, %46, %47, %48, %49, %50, %51, %52, %53, %54, %55}, "
      "da, db, p, 1, 1, %59, %60;\n}\n"
      : "+f"(d[0]), "+f"(d[1]), "+f"(d[2]), "+f"(d[3]), "+f"(d[4]), "+f"(d[5]), "+f"(d[6]),
        "+f"(d[7]), "+f"(d[8]), "+f"(d[9]), "+f"(d[10]), "+f"(d[11]), "+f"(d[12]), "+f"(d[13]),
        "+f"(d[14]), "+f"(d[15]), "+f"(d[16]), "+f"(d[17]), "+f"(d[18]), "+f"(d[19]), "+f"(d[20]),
        "+f"(d[21]), "+f"(d[22]), "+f"(d[23]), "+f"(d[24]), "+f"(d[25]), "+f"(d[26]), "+f"(d[27]),
        "+f"(d[28]), "+f"(d[29]), "+f"(d[30]), "+f"(d[31]), "+f"(d[32]), "+f"(d[33]), "+f"(d[34]),
        "+f"(d[35]), "+f"(d[36]), "+f"(d[37]), "+f"(d[38]), "+f"(d[39]), "+f"(d[40]), "+f"(d[41]),
        "+f"(d[42]), "+f"(d[43]), "+f"(d[44]), "+f"(d[45]), "+f"(d[46]), "+f"(d[47]), "+f"(d[48]),
        "+f"(d[49]), "+f"(d[50]), "+f"(d[51]), "+f"(d[52]), "+f"(d[53]), "+f"(d[54]), "+f"(d[55])
      : "r"(descA), "r"(descB), "r"(scaleD), "n"(TA), "n"(TB), "n"(TB ? 8 : 0x40000040));
}

template <int T>
__device__ __forceinline__ void pack_half(float (&pk)[56], const float (&a)[56]) {
#pragma unroll
  for (int i = 0; i < 28; i++) pk[28 * T + i] = __uint_as_float(pack_bf16(a[2 * i], a[2 * i + 1]));
}
template <int T>
__device__ __forceinline__ void fence_half(float (&pk)[56]) {
#pragma unroll
  for (int i = 0; i < 28; i++) asm volatile("" : "+f"(pk[28 * T + i])::"memory");
}
template <int T>
__device__ __forceinline__ void store_half(uint32_t addr, const float (&pk)[56]) {
#pragma unroll
  for (int q = 0; q < 7; q++) {
    const float* r = pk + 28 * T + 4 * q;
    stsm_x4_t(addr + T * PANEL + q * 2048, __float_as_uint(r[0]), __float_as_uint(r[1]), __float_as_uint(r[2]), __float_as_uint(r[3]));
  }
}

template <int T>
__device__ __forceinline__ void q_half(uint32_t addr, float (&pk)[56], const float (&a)[56], int never) {
#pragma unroll
  for (int q = 0; q < 7; q++) {
    uint32_t r[4];
#pragma unroll
    for (int i = 0; i < 4; i++) {
      r[i] = pack_bf16(a[8 * q + 2 * i] * kQScale, a[8 * q + 2 * i + 1] * kQScale);
      pk[28 * T + 4 * q + i] = __uint_as_float(r[i]);
    }
    if (q < 6 && (Q_PIN >> q & 1)) stsm_x4_t_pin(addr + T * PANEL + q * 2048, r[0], r[1], r[2], r[3], never, 32 + 2 * (7 * T + q));
    else stsm_x4_t(addr + T * PANEL + q * 2048, r[0], r[1], r[2], r[3]);
  }
}

__device__ __forceinline__ float bf_lo(uint32_t u) { return __uint_as_float(u << 16); }
__device__ __forceinline__ float bf_hi(uint32_t u) { return __uint_as_float(u & 0xFFFF0000u); }

__device__ __forceinline__ void fma8(float* o, float a, const uint4& w, float c) {
  o[0] = fmaf(a, bf_lo(w.x), o[0] * c), o[1] = fmaf(a, bf_hi(w.x), o[1] * c);
  o[2] = fmaf(a, bf_lo(w.y), o[2] * c), o[3] = fmaf(a, bf_hi(w.y), o[3] * c);
  o[4] = fmaf(a, bf_lo(w.z), o[4] * c), o[5] = fmaf(a, bf_hi(w.z), o[5] * c);
  o[6] = fmaf(a, bf_lo(w.w), o[6] * c), o[7] = fmaf(a, bf_hi(w.w), o[7] * c);
}
__device__ __forceinline__ void slow_rows(uint4* qrow, int tq, const __nv_bfloat16* xp, const __nv_bfloat16* wp,
                                          const __nv_bfloat16* kp, const __nv_bfloat16* vp, __nv_bfloat16* op) {
  if (tq >= NQ) return;
#pragma unroll 1
  for (int c = 0; c < 16; c++) {
    float q[8] = {};
#pragma unroll 1
    for (int k = 0; k < kD; k++)
      fma8(q, __bfloat162float(xp[tq * kD + k]), __ldg(reinterpret_cast<const uint4*>(wp + k * (kH * kDh)) + c), 1.f);
    qrow[c * 128] = make_uint4(pack_bf16(q[0] * kQScale, q[1] * kQScale), pack_bf16(q[2] * kQScale, q[3] * kQScale),
                               pack_bf16(q[4] * kQScale, q[5] * kQScale), pack_bf16(q[6] * kQScale, q[7] * kQScale));
  }
#pragma unroll 1
  for (int pass = 0; pass < 4; pass++) {
    float o[32] = {}, m = -INFINITY, l = 0.f;
#pragma unroll 1
    for (int key = 0; key < kSk; key++) {
      const uint4* kr = reinterpret_cast<const uint4*>(kp + key * kDh);
      const uint4* vr = reinterpret_cast<const uint4*>(vp + key * kDh) + 4 * pass;
      float s = 0.f;
#pragma unroll 1
      for (int c = 0; c < 16; c++) {
        const uint4 q = qrow[c * 128], k = __ldg(kr + c);
        s = fmaf(bf_lo(q.x), bf_lo(k.x), s); s = fmaf(bf_hi(q.x), bf_hi(k.x), s);
        s = fmaf(bf_lo(q.y), bf_lo(k.y), s); s = fmaf(bf_hi(q.y), bf_hi(k.y), s);
        s = fmaf(bf_lo(q.z), bf_lo(k.z), s); s = fmaf(bf_hi(q.z), bf_hi(k.z), s);
        s = fmaf(bf_lo(q.w), bf_lo(k.w), s); s = fmaf(bf_hi(q.w), bf_hi(k.w), s);
      }
      const float mn = fmaxf(m, s);
      const float ms = (mn == -INFINITY) ? 0.f : mn;
      const float corr = ex2(m - ms), p = ex2(s - ms);
      l = l * corr + p;
      m = mn;
      const float pb = __bfloat162float(__float2bfloat16(p));
#pragma unroll
      for (int c = 0; c < 4; c++) fma8(o + 8 * c, pb, __ldg(vr + c), corr);
    }
    const float sc = __fdividef(1.f, l);
    __nv_bfloat16* dst = op + (pass >> 1) * PANEL + (pass & 1) * 3584 + (tq >> 3) * 64 + (tq & 7);
#pragma unroll
    for (int d = 0; d < 32; d++) dst[(d >> 3) * 896 + (d & 7) * 8] = __float2bfloat16(o[d] * sc);
  }
}

__device__ __forceinline__ uint32_t launch_epoch() { return atomicAdd(&g_ticket, 1u) / gridDim.x; }

__global__ void __cluster_dims__(2, 1, 1) __launch_bounds__(384, 1) mha_fused_kernel(const __grid_constant__ Params prm) {
  extern __shared__ __align__(1024) unsigned char smem_raw[];

  const uint32_t sb = (smem_u32(smem_raw) + 1023u) & ~1023u;
  const uint32_t full0 = sb + SM_BAR, empty0 = full0 + 8 * NBAR, sfull0 = empty0 + 8 * NBAR;
  const uint32_t cred0 = sfull0 + 32, redo0 = cred0 + 64, epoch_addr = redo0 + 8, go_bar = redo0 + 16, ok_bar = redo0 + 24;
  const uint32_t rank = blockIdx.x & 1, pair = blockIdx.x >> 1;
  const uint32_t head = prm.head[pair];
  const int u_begin = head & 1023, u_end = u_begin + ((head >> 10) & 31);
  const uint32_t delay = ((head >> 15) & 255) * 256;
  const int tid = threadIdx.x;
  const int wid = __shfl_sync(0xffffffffu, tid >> 5, 0), wg = wid >> 2;

  if (wg == 2) {
    asm volatile("setmaxnreg.dec.sync.aligned.u32 %0;" ::"n"(504 - 2 * CREGS));
    const int warp = wid & 3, lane = tid & 31;
    bar_sync(0, 384);
    asm volatile("barrier.cluster.arrive.relaxed.aligned;" ::: "memory");
    if (warp < 3 && delay)
      asm volatile(
          "{\n.reg .pred p, q;\n.reg .u32 t0, t;\nmov.u32 t0, %%clock;\n"
          "SPIN:\nnanosleep.u32 100;\nmov.u32 t, %%clock;\nsub.u32 t, t, t0;\nsetp.lt.u32 p, t, %0;\n"
          "vote.sync.all.pred q, p, 0xffffffff;\n@q bra.uni SPIN;\n}" ::"r"(delay));
    auto slot_addr = [&](uint32_t i) { return sb + SM_RING + ring_slot(i) * SLOT; };
    auto full_bar = [&](uint32_t i) { return full0 + 8 * ring_slot(i); };
    const int count = (head >> 10) & 31;
    if (warp == 0) {
      uint32_t it = 0, prev = 0, code = head >> 23;
      auto acquire = [&](uint32_t i) { mbar_wait_warp(empty0 + 8 * ring_slot(i), ring_par(i) ^ 1); };
      uint32_t rblk = 0, rleft = 0;
      auto block_read = [&]() {
        asm volatile(ELECTED "red.relaxed.gpu.global.add.u32 [%0], 1;\n}" ::"l"(&g_rd[prm.blk[rblk] & 511]) : "memory");
        rblk++;
        rleft--;
      };
#pragma unroll 1
      for (int n = 1; n <= count; n++) {
        const uint32_t pat = unit_pattern(code, prev);
        const Unit u = decode_unit(code, rank);
        const int br = u.g >> 4;
        const CUtensorMap* mw = (u.attn ? prm.wq : prm.wo) + br;
        const int nslab = u.nslab;
#pragma unroll 1
        for (int k = 0, pos = 0; k < nslab; k++) {
          const uint32_t i = it + (pos == 0);
          acquire(i);
          e_expect_tx(full_bar(i), SLOT);
          tma_ld3(slot_addr(i), mw, u.h0 * 256 + k * 64, u.hc * 2, full_bar(i), kEvictNormal);
          if (rleft && (k == 2 || k == 10 || (k >= 12 && (k & 3) == 0))) {
#pragma unroll 1
            do block_read();
            while (rleft && k == 2);
          }
          if (!u.attn && k == 4) rblk = u.g * 16 + u.h0, rleft = nslab >> 2;
          it = i + 1 + (pos == 0);
          pos = next_pos(pos, k, pat);
        }
        if (u.attn) {
          const int row0 = ((u.g & 15) * kH + u.hc) * kSk;
#pragma unroll 1
          for (int j = 0; j < kSk / 32; j++, it++) {
            acquire(it);
            e_expect_tx(full_bar(it), SLOT);
            const int isv = j == 31 || (j > 0 && !(j & 1));
            tma_ld3(slot_addr(it), &prm.kv[2 * isv + br], row0 + (((j + 1) >> 1) - isv) * 64, 0, full_bar(it), kEvictFirst);
            if (j == kSk / 32 - 2) e_arrive(go_bar, 1);
          }
        }
        prev = code;
        code = prm.unit[u_begin + n];
      }
      if (rleft) {
        acquire(it + NSLOT - 1);
#pragma unroll 1
        while (rleft) block_read();
      }
    } else if (warp < 3) {
      asm volatile("barrier.cluster.wait.acquire.aligned;" ::: "memory");
      const int w = warp == 1 ? rank : rank ^ 1;
      uint32_t it = 0, nc = 0, pph = 0, go_ph = 0, prev = 0, code = head >> 23;
      uint32_t peer_cred0;
      asm("mapa.shared::cluster.u32 %0, %1, %2;" : "=r"(peer_cred0) : "r"(cred0), "r"(rank ^ 1));
#pragma unroll 1
      for (int n = 1; n <= count; n++) {
        const uint32_t pat = unit_pattern(code, prev);
        Unit u = decode_unit(code, rank);
        const CUtensorMap* mx = u.attn ? &prm.x[u.g >> 4] : &prm.o_ld;
        const int nslab = u.nslab;
        const bool polls = !u.attn && (warp == 1 || !u.mc);
        uint32_t done = 0, ready = 0;
        if (polls) {
          asm volatile("ld.volatile.shared.u32 %0, [%1];" : "=r"(done) : "r"(epoch_addr) : "memory");
          done *= 2;
        }
        const unsigned int* flags = g_cnt + u.g * 16 + (lane & 15);
        const uint64_t xpol = u.attn ? kEvictNormal : kEvictFirst;
        int xcol = 0, xrow = (u.g & 15) * kSq + w * NQ;
#pragma unroll 1
        for (int k = 0, pos = 0; k < nslab; k++) {
          if (polls && (k & 2) == 0) {
            const uint32_t hp = u.h0 + (k >> 2);
            if ((k & 1) == 0) {
              if (!(ready >> hp & 1)) ready = flags_wait(flags, done, 1u << hp);
              xrow = (prm.blk[u.g * 16 + hp] & 511) * (4 * kSq) + w * NQ;
            } else if (!(ready >> hp & 2)) {
              ready = flags_wait(flags, done, 0);
            }
          }
          const uint32_t i = it + 2 * w, q = pos - 1;
          const uint32_t fbar = full0 + 8 * (pos == 0 ? ring_slot(i) : NSLOT + 4 * w + q);
          const uint32_t dst = pos == 0 ? slot_addr(i) : sb + SM_PANEL + (4 * w + q) * PANEL;
          const uint32_t par = (pos == 0 ? ring_round(i) : pph >> q) & 1;
          pph ^= pos == 0 ? 0u : 1u << q;
          it += 1 + 2 * (pos == 0);
          pos = next_pos(pos, k, pat);
          mbar_wait_warp(fbar + 8 * NBAR, par ^ 1);
          e_expect_tx(fbar, PANEL);
          if (!u.mc) {
            tma_ld2(dst, mx, xcol, xrow, fbar, xpol);
          } else {
            if (warp == 1) {
              if (it > 10) mbar_wait_warp(cred0 + 8 * (nc & 7), (nc >> 3) & 1);
              tma_ld2_mc(dst, mx, xcol, xrow, fbar, xpol);
            } else if (it > 10) {
              asm volatile(ELECTED "mbarrier.arrive.shared::cluster.b64 _, [%0];\n}" ::"r"(peer_cred0 + 8 * (nc & 7)) : "memory");
            }
            nc += it > 10;
          }
          xcol += u.attn ? 64 : 0;
          xrow += u.attn ? 0 : kSq;
        }
        if (u.attn) {
          mbar_wait_warp(go_bar, go_ph);
          go_ph ^= 1;
          it += kSk / 32;
        }
        prev = code;
        code = prm.unit[u_begin + n];
      }
    } else {
      uint32_t epoch = 0, prev = 0;
      if (lane == 0) epoch = launch_epoch();
      epoch = __shfl_sync(0xffffffffu, epoch, 0);
      asm volatile("st.volatile.shared.u32 [%0], %1;" ::"r"(epoch_addr), "r"(epoch + 1) : "memory");
      auto publish = [&](unsigned int* p) {
        __syncwarp();
        asm volatile(ELECTED "red.release.gpu.global.add.u32 [%0], 1;\n}" ::"l"(p) : "memory");
      };
#pragma unroll 1
      for (int n = 0; n < count; n++) {
        const uint32_t code = prm.unit[u_begin + n], ph = n & 1;
        if (!(code & 0x8000u)) {
          const uint32_t blk = prm.blk[code & 511], gen = (blk >> 9) & 7;
          if (gen > 0) flag_wait(&g_rd[blk & 511], 5 * (epoch * (blk >> 12) + gen));
        }
        __syncwarp();
        e_arrive(ok_bar, 1);
        const bool clear = (code & 0xA000u) == 0x2000u;
        const uint32_t oc = clear ? prm.unit[u_begin + n + 1] : code;
        const Unit u = decode_unit(oc, rank);
        const int row = (u.g & 15) * kSq, cb = (u.g >> 4) * 10 + u.hc * 2;
        unsigned int* pc = g_pc + (oc >> 8 & 127) * 32 + rank;
        if (!(code & 0x8000u)) {
          if (clear) {
            uint4* o = reinterpret_cast<uint4*>(prm.op + (row + (lane >> 4)) * (2 * kD) + cb * 64) + (lane & 15);
#pragma unroll 1
            for (int r = 0; r < kSq / 2; r++, o += 4 * kD / 8) {
              *o = make_uint4(0, 0, 0, 0);
              __nanosleep(40);
            }
            publish(pc + 2 * (oc & 15));
          }
#pragma unroll 1
          for (int q = 0; q < 4; q++) mbar_wait_warp(sfull0 + 8 * q, ph);
          publish(&g_cnt[code & 511]);
        } else {
          const bool cleared = (prev & 0xA000u) == 0x2000u;
          if (u.h0) flag_wait(pc + 2 * (u.h0 - 1), epoch + 1);
          asm volatile("fence.proxy.async.global;" ::: "memory");
#pragma unroll 1
          for (int q = 0; q < 4; q++) {
            const int w = q & 1, t = q >> 1;
            mbar_wait_warp(sfull0 + 8 * q, ph);
            fence_async_smem();
#pragma unroll 1
            for (int r = 0; r < NQ; r += ST_ROWS) {
              tma_st3(&prm.out, row + w * NQ + r, cb + t, sb + SM_PANEL + (4 * w + 2 + t) * PANEL + r * 128, u.h0 || cleared);
              asm volatile("cp.async.bulk.commit_group;" ::: "memory");
              if (n + 1 < count) asm volatile("cp.async.bulk.wait_group.read 0;" ::: "memory");
            }
            __syncwarp();
            e_arrive(empty0 + 8 * (NSLOT + 4 * w + 2 + t), 2);
          }
          if ((code & 15) != 15 && !cleared) {
            asm volatile("cp.async.bulk.wait_group 0;" ::: "memory");
            asm volatile("fence.proxy.async.global;" ::: "memory");
            publish(pc + 2 * (code & 15));
          }
        }
        prev = code;
      }
      asm volatile("cp.async.bulk.wait_group 0;" ::: "memory");
    }
  } else {
    const int tq = tid & 127, lane = tid & 31, warp = tq >> 5;
    if (tid == 0) {
#pragma unroll
      for (int i = 0; i < NBAR; i++) {
        mbar_init(full0 + 8 * i, 1);
        mbar_init(empty0 + 8 * i, 2);
      }
#pragma unroll
      for (int i = 0; i < 12; i++) mbar_init(sfull0 + 8 * i, i < 4 ? 4 : 1);
      mbar_init(go_bar, 1);
      mbar_init(ok_bar, 1);
      asm volatile("st.shared.v4.u32 [%0], {%1, %1, %1, %1};" ::"r"(redo0), "r"(0) : "memory");
      asm volatile("fence.mbarrier_init.release.cluster;" ::: "memory");
    }
    bar_sync(0, 384);
    asm volatile("barrier.cluster.arrive.relaxed.aligned;" ::: "memory");
    asm volatile("setmaxnreg.inc.sync.aligned.u32 %0;" ::"n"(CREGS));
    const uint32_t stage = sb + SM_PANEL + wg * 4 * PANEL;
    const uint32_t st_q = __shfl_sync(
        0xffffffffu, stage + ((lane >> 4) * 8 + (lane & 7)) * 128 + (((2 * warp + ((lane >> 3) & 1)) ^ (lane & 7)) << 4), lane);
    const uint32_t st_p = st_q + 2 * PANEL;
    const uint32_t dq = mk_desc(stage), dring = mk_desc(sb + SM_RING);
    float acc[2][56], s[56] = {};
    const int never = (sb >> 24) & ~1u;
    uint32_t it = 0, pph = 0;
    auto wait_full = [&](uint32_t i) { mbar_wait_warp(full0 + 8 * ring_slot(i), ring_par(i)); };
    auto test = [&](uint32_t bar, uint32_t par) { return mbar_test_if(bar, par, warp == 0); };
    auto probe = [&](uint32_t i) { return test(full0 + 8 * ring_slot(i), ring_par(i)); };
    auto release = [&](uint32_t i) { mbar_arrive1_if(empty0 + 8 * ring_slot(i), tq == 0); };
    auto slot_desc = [&](uint32_t i) { return dring + ring_slot(i) * (SLOT >> 4); };
    if (wg == 1) bar_arrive(1, 256);

    struct Fin {
      uint32_t rp[16], z;
      char* dst;
    };
    uint32_t ps[14] = {};
    auto step_sums = [&]() {
#pragma unroll
      for (int q = 0; q < 3; q++) stsm_x4_t(st_p + q * 2048, ps[2 * q], ps[2 * q + 7], ps[2 * q + 1], ps[2 * q + 8]);
      asm volatile("stmatrix.sync.aligned.m8n8.x2.trans.shared.b16 [%0], {%1, %2};" ::"r"(st_p + 3 * 2048), "r"(ps[6]), "r"(ps[13])
                   : "memory");
    };
    auto step_finite = [&](Fin& f) {
      uint32_t z[4] = {0, 0, 0, 0};
#pragma unroll
      for (int i = 0; i < 28; i++)
        asm volatile("fma.rn.bf16x2 %0, %1, %2, %0;" : "+r"(z[i & 3]) : "r"(__float_as_uint(s[2 * i])), "r"(__float_as_uint(s[2 * i + 1])));
      asm volatile("add.rn.bf16x2 %0, %0, %1;" : "+r"(z[0]) : "r"(z[1]));
      asm volatile("add.rn.bf16x2 %0, %0, %1;" : "+r"(z[2]) : "r"(z[3]));
      asm volatile("add.rn.bf16x2 %0, %1, %2;" : "=r"(f.z) : "r"(z[0]), "r"(z[2]));
    };
    auto rows_addr = [&]() {
      const uint32_t q = min(tq, NQ - 1), hi = q >= 56, n = q - 56 * hi;
      return stage + 2 * PANEL + n * 128 + ((hi ^ (n & 7)) << 4);
    };
    auto rows_load = [&](Fin& f, uint32_t a) {
#pragma unroll
      for (int c = 0; c < 4; c++)
        asm volatile("ld.shared.v4.u32 {%0, %1, %2, %3}, [%4];"
                     : "=r"(f.rp[4 * c]), "=r"(f.rp[4 * c + 1]), "=r"(f.rp[4 * c + 2]), "=r"(f.rp[4 * c + 3])
                     : "r"(a ^ (c << 5))
                     : "memory");
    };
    auto step_rows = [&](const Fin& f, bool live) {
      const uint32_t q = min(tq, NQ - 1);
      float l = 0.f, l2 = 0.f;
#pragma unroll
      for (int i = 0; i < 8; i++) {
        uint32_t v;
        asm("add.rn.bf16x2 %0, %1, %2;" : "=r"(v) : "r"(f.rp[2 * i]), "r"(f.rp[2 * i + 1]));
        l += bf_lo(v), l2 += bf_hi(v);
      }
      l += l2;
      float r;
      asm("rcp.approx.ftz.f32 %0, %1;" : "=f"(r) : "f"(l));
      asm volatile("st.shared.u16 [%0], %1;" ::"r"(sb + SM_RCP + wg * 320 + (q >> 1 & 3) * 80 + (q >> 3) * 4 + (q & 1) * 2),
                   "h"((uint16_t)pack_bf16(r, r))
                   : "memory");
      const bool bad = !(l >= 9.094947017729282e-13f && l <= 1.329227995784916e36f) || (((f.z & 0x7F807F80u) + 0x00800080u) & 0x80008000u);
      asm volatile("{\n.reg .pred p;\nsetp.ne.u32 p, %1, 0;\n@p st.shared.u32 [%0], %1;\n}" ::"r"(redo0 + 4 * wg), "r"((uint32_t)(live && bad))
                   : "memory");
    };
    auto step_scales = [&](Fin& f) {
#pragma unroll
      for (int c = 0; c < 4; c++)
        asm volatile("ld.shared.v4.u32 {%0, %1, %2, %3}, [%4];"
                     : "=r"(f.rp[4 * c]), "=r"(f.rp[4 * c + 1]), "=r"(f.rp[4 * c + 2]), "=r"(f.rp[4 * c + 3])
                     : "r"(sb + SM_RCP + wg * 320 + (lane & 3) * 80 + c * 16)
                     : "memory");
    };
    auto o_base = [&](uint32_t u) {
      return reinterpret_cast<char*>(g_o) + (size_t)((((prm.blk[u & 511] & 511u) * 4 + rank * 2) * 2 + wg) * (uint32_t)PANEL);
    };
    auto step_write = [&](const Fin& f, int lo, int hi) {
#pragma unroll
      for (int i = lo; i < hi; i++) {
        uint32_t v = __float_as_uint(s[i]);
        asm("mul.rn.bf16x2 %0, %0, %1;" : "+r"(v) : "r"(f.rp[(i % 28) >> 1]));
        s[i] = __uint_as_float(v);
        asm volatile("st.global.u32 [%0], %1;" ::"l"(f.dst + (i / 28) * 2 * PANEL + (i & 1) * 1792 + ((i % 28) >> 1) * 128), "r"(v) : "memory");
      }
    };
    auto keep_alive = [&](int lo, int hi, int c) {
      if (never == c) {
#pragma unroll
        for (int i = lo; i < hi; i++) asm volatile("st.shared.f32 [%0], %1;" ::"r"(stage + 4 * i), "f"(s[i]) : "memory");
        pin_order(never, c);
      }
    };
    auto step_signal = [&](int t) {
      __syncwarp();
      mbar_arrive1_if(sfull0 + 8 * (2 * t + wg), lane == 0);
    };
    auto free_panel = [&](int q) { mbar_arrive1_if(empty0 + 8 * (NSLOT + 4 * wg + q), tq < 2); };
    auto read_verdict = [&]() {
      uint32_t redo;
      asm volatile("ld.shared.u32 %0, [%1];" : "=r"(redo) : "r"(redo0 + 4 * wg) : "memory");
      return redo;
    };
    auto step_redo = [&](uint32_t prev) {
      asm volatile("" : "+r"(prev));
      bar_sync(3 + wg, 128);
      if (tq == 0) asm volatile("st.shared.u32 [%0], %1;" ::"r"(redo0 + 4 * wg), "r"(0) : "memory");
      const Unit u = decode_unit(prev & 511, rank);
      const int br = u.g >> 4, b = u.g & 15;
      const size_t off = (size_t)(b * kH + u.hc) * kSk * kDh;
      slow_rows(g_qrow + (blockIdx.x * 2 + wg) * (16 * 128) + tq, tq, prm.xp[br] + (b * kSq + wg * NQ) * kD, prm.wp[br] + u.hc * kDh,
                prm.kp[br] + off, prm.vp[br] + off, reinterpret_cast<__nv_bfloat16*>(o_base(prev)));
#pragma unroll
      for (int i = 0; i < 56; i++) s[i] = 0.f;
    };
    auto issue_slab = [&](uint32_t da, uint32_t db, int accum, auto split, auto tb) {
      constexpr int TB = tb.value, KS = TB ? 224 : 2;
      if (TB) db += 111 << 16;
      if (split.value == 1) {
#pragma unroll
        for (int t = 0; t < 2; t++) {
#pragma unroll
          for (int kk = 0; kk < 4; kk++) {
            if (t == 1 && kk == 2) bar_arrive(2 - wg, 256);
            wgmma_n112<1, TB>(acc[t], da + t * 512 + kk * 128, db + kk * KS, 1);
          }
          wgmma_commit();
        }
      } else {
#pragma unroll
        for (int kk = 0; kk < 4; kk++) {
          if (kk == 3) bar_arrive(2 - wg, 256);
          wgmma_n112<1, TB>(acc[0], da + kk * 128, db + kk * KS, kk > 0 ? 1 : accum);
          wgmma_n112<1, TB>(acc[1], da + 512 + kk * 128, db + kk * KS, kk > 0 ? 1 : accum);
        }
        wgmma_commit();
      }
    };

    uint32_t code = head >> 23, prev = 0, pend = 0, uph = 0;
    uint32_t da = slot_desc(1), db = slot_desc(2 * wg);
    auto next_unit = [&](bool block) {
      da = slot_desc(it + 1), db = slot_desc(it + 2 * wg);
      if (block) {
        if (!__all_sync(0xffffffffu, probe(it + 1) & probe(it + 2 * wg))) {
          wait_full(it + 1);
          wait_full(it + 2 * wg);
        }
      }
    };
    wait_full(1);
    wait_full(2 * wg);
    for (int left = (head >> 10) & 31; left > 0; left--) {
      const int ui = u_end - left;
      uint32_t nxt;
      bool defer;
      auto peek = [&]() {
        const uint32_t cur = prm.unit[ui];
        nxt = __shfl_sync(0xffffffffu, (uint32_t)prm.unit[ui + 1], 0);
        defer = left > 1 && (!(nxt & 0x8000u) || (cur & 0xC000u) == 0x4000u);
      };
      const bool out = code & 0x8000u;
      uint32_t rel = 0;
      auto retire = [&]() {
        wgmma_wait<0>();
        fence_regs(acc[0]);
        fence_regs(acc[1]);
        mbar_arrive1_if(rel, rel);
        rel = 0;
      };
      auto turn = [&](int accum, auto mode, auto tb, auto first) {
        bar_sync(1 + wg, 256);
        if (!first.value) retire();
        wgmma_fence();
        issue_slab(da, db, accum, mode, tb);
      };
      auto take_turn = [&](int accum, auto mode, auto first) {
        if (out) turn(accum, mode, IntC<1>{}, first);
        else turn(accum, mode, IntC<0>{}, first);
      };
      Fin f;
      int k = 0;
      const bool staged = pend == 2;
      if (out ? pend == 1 : !staged) {
        uint32_t redo = 0;
        static_for<0, 8>([&](auto kc) {
          constexpr int k = kc.value;
          take_turn(k > 0, IntC<0>{}, BoolC<k == 0>{});
          if (k >= 4) keep_alive(w_cut(k - 4), w_cut(k - 3), 62 + 2 * k);
          if (k == 0 && never == 62) {
            step_sums();
            pin_order(never, 62);
          }
          if (k == 2) step_scales(f);
          constexpr int p0 = x_pos(0, k), p1 = x_pos(0, k + 1), o0 = x_off(0, k), o1 = x_off(0, k + 1);
          const uint32_t rw = empty0 + 8 * ring_slot(it + o0 + (p0 == 0));
          const uint32_t rx = empty0 + 8 * (p0 == 0 ? ring_slot(it + o0 + 2 * wg) : NSLOT + 4 * wg + p0 - 1);
          const uint32_t wi = it + o1 + (p1 == 0), xi = it + o1 + 2 * wg;
          const uint32_t xbar = full0 + 8 * (p1 == 0 ? ring_slot(xi) : NSLOT + 4 * wg + p1 - 1);
          const uint32_t xpar = (p1 == 0 ? ring_round(xi) : pph >> (p1 == 0 ? 0 : p1 - 1)) & 1;
          if constexpr (p1 != 0) pph ^= 1u << (p1 - 1);
          uint32_t okp = probe(wi) & test(xbar, xpar);
          if (k == 2) okp &= test(ok_bar, uph ^ pend);
          rel = pick(tq == 0, rw, pick(tq < 3 && (k < 6 || out), rx, 0));
          if (k == 0) {
            rows_load(f, rows_addr());
            step_finite(f);
          }
          if (k == 1) {
            mbar_arrive1_if(empty0 + 8 * (NSLOT + 4 * wg + 2), tq < 2 && pend);
            step_rows(f, pend);
          }
          if (k == 2) f.dst = o_base(prev) + warp * 3584 + lane * 4;
          if (k == 6) redo = read_verdict();
          if (k >= 3 && pend) step_write(f, w_cut(k - 3), w_cut(k - 2));
          if (k == 7) {
            if (__any_sync(0xffffffffu, redo)) step_redo(prev);
            __syncwarp();
            mbar_arrive1_if(sfull0 + 8 * (2 * lane + wg), lane < 2 && pend);
          }
          const bool ok = __all_sync(0xffffffffu, okp);
          da = slot_desc(wi);
          db = p1 == 0 ? slot_desc(xi) : dq + (p1 - 1) * (PANEL >> 4);
          if (!ok) {
            retire();
            wait_full(wi);
            mbar_wait_warp(xbar, xpar);
            if (k == 2) mbar_wait_warp(ok_bar, uph ^ pend);
          }
        });
        k = 8;
      }
      const int nslab = unit_slabs(code);
      uint32_t pos = k ? 3 : 0, wi = it + (k ? 12 : 1), xbar = full0 + 8 * (k ? NSLOT + 4 * wg + 2 : ring_slot(it + 2 * wg));
      const int kend = out ? nslab - 1 : 8;
      if (k < kend) {
        uint32_t r = it + (k ? 13 : 3);
        const uint32_t pat = staged ? kPat1 : kPat0;
        const uint32_t keep_pos = out ? 3 : 1;
        const int keep_k = nslab == 8 ? 4 : nslab - 5;
#pragma unroll 1
        do {
          take_turn(k > 0, IntC<0>{}, BoolC<false>{});
          rel = pick(tq == 0, empty0 + 8 * ring_slot(wi), pick(tq < 3 && (pos < keep_pos || k < keep_k), xbar + 8 * NBAR, 0));
          pos = next_pos(pos, k, pat);
          const bool ring = pos == 0;
          const uint32_t i = r + 2 * wg, q = pos - 1;
          wi = ring ? r + 1 : r;
          xbar = full0 + 8 * (ring ? ring_slot(i) : NSLOT + 4 * wg + q);
          const uint32_t xpar = (ring ? ring_round(i) : pph >> q) & 1;
          da = slot_desc(wi);
          db = ring ? slot_desc(i) : dq + q * (PANEL >> 4);
          pph ^= ring ? 0u : 1u << q;
          r += ring ? 3 : 1;
          const bool job = staged && k < 2;
          if (job || !__all_sync(0xffffffffu, probe(wi) & test(xbar, xpar))) {
            if (!job) {
              retire();
            } else {
              if (k == 0) {
                mbar_wait_warp(ok_bar, uph ^ 1);
                store_half<0>(st_p, s);
              } else {
                store_half<1>(st_p, s);
              }
              step_signal(k);
            }
            wait_full(wi);
            mbar_wait_warp(xbar, xpar);
          }
        } while (++k < kend);
      }
      if (!out) {
        it += staged ? x_off(1, 10) : x_off(0, 10);
        {
          const uint32_t x9 = full0 + 8 * (NSLOT + 4 * wg + 3), p9 = pph >> 3 & 1, d9 = slot_desc(it - 1);
          pph ^= 8;
          if (!__all_sync(0xffffffffu, probe(it - 1) & test(x9, p9))) {
            retire();
            wait_full(it - 1);
            mbar_wait_warp(x9, p9);
          }
          bar_sync(1 + wg, 256);
          retire();
          wgmma_fence();
#pragma unroll
          for (int t = 0; t < 2; t++) {
#pragma unroll
            for (int kk = 0; kk < 8; kk++)
              wgmma_n112<1>(acc[t], (kk < 4 ? da : d9) + t * 512 + (kk & 3) * 128, db + t * never + (kk >> 2) * (PANEL >> 4) + (kk & 3) * 2, 1);
            wgmma_commit();
          }
          bar_arrive(2 - wg, 256);
          keep_alive(w_cut(4), w_cut(5), 80);
          const bool ok = __all_sync(0xffffffffu, probe(it));
          rel = pick(tq < 2, empty0 + 8 * pick(tq == 0, ring_slot(it - 2), ring_slot(it - 1)), 0);
          da = slot_desc(it);
          wgmma_wait<1>();
          fence_regs(acc[0]);
          q_half<0>(st_q, s, acc[0], never);
          wgmma_wait<0>();
          fence_regs(acc[1]);
          q_half<1>(st_q, s, acc[1], never);
          mbar_arrive1_if(rel, rel);
          if (!ok) wait_full(it);
        }
        fence_async_smem();
        float l[28];
        auto issue_s = [&](uint32_t dk, int accum) {
          wgmma_fence();
#pragma unroll
          for (int kk = 0; kk < 8; kk++)
            wgmma_n112<0>(s, dk + (kk >> 2) * 512 + (kk & 3) * 2, dq + (kk >> 2) * (PANEL >> 4) + (kk & 3) * 2, kk > 0 ? 1 : accum);
          wgmma_commit();
        };
        auto add_sums = [&]() {
#pragma unroll
          for (int jj = 0; jj < 14; jj++)
            asm volatile("{\n.reg .b32 t;\nshl.b32 t, %2, 16;\nadd.f32 %0, %0, t;\nand.b32 t, %2, 0xffff0000;\nadd.f32 %1, %1, t;\n}"
                         : "+f"(l[2 * jj]), "+f"(l[2 * jj + 1])
                         : "r"(ps[jj]));
        };
        auto softmax = [&](uint32_t par, int pin0) {
          const uint32_t pa = st_p + par * PANEL;
#pragma unroll
          for (int i = 0; i < 8 + SM_OFF; i++) s[i] = ex2(s[i]);
#pragma unroll
          for (int jj = 0; jj < 7; jj++) {
            const float* e = s + 8 * jj;
#pragma unroll
            for (int i = 8 * jj + 8 + SM_OFF; i < 8 * jj + 16 + SM_OFF; i++)
              if (i < 56) s[i] = ex2(s[i]);
            const uint32_t p0 = pack_bf16(e[0], e[1]), p1 = pack_bf16(e[2], e[3]), p2 = pack_bf16(e[4], e[5]), p3 = pack_bf16(e[6], e[7]);
            stsm_x4_t_pin(pa + jj * 2048, p0, p1, p2, p3, never, pin0);
            asm("add.rn.bf16x2 %0, %1, %2;" : "=r"(ps[2 * jj]) : "r"(p0), "r"(p1));
            asm("add.rn.bf16x2 %0, %1, %2;" : "=r"(ps[2 * jj + 1]) : "r"(p2), "r"(p3));
          }
        };
        bar_sync(1 + wg, 256);
        issue_s(da, never);
        bar_arrive(2 - wg, 256);
        {
#pragma unroll
          for (int i = 0; i < 28; i++) asm volatile("mov.b32 %0, 0;" : "=f"(l[i]));
          peek();
          const bool ok = __all_sync(0xffffffffu, probe(it + 1));
          da = slot_desc(it + 1);
          wgmma_wait_pin<0>(never, 180);
          fence_regs(s);
          release(it);
          softmax(0, 176);
          if (!ok) wait_full(it + 1);
        }
        it += 1;
#pragma unroll 1
        for (int j = 1; j < 16; j++) {
          fence_async_smem();
          bar_sync(1 + wg, 256);
          issue_s(da, 0);
          pin_order(never, 2 * j + 128);
          const uint32_t okv = mbar_test(full0 + 8 * ring_slot(it + 1), ring_par(it + 1));
          const uint32_t okk = probe(it + 2);
          da = slot_desc(it + 2);
          add_sums();
          const bool ok = __all_sync(0xffffffffu, okk);
          if (!__all_sync(0xffffffffu, okv)) wait_full(it + 1);
          {
            const uint32_t dv = slot_desc(it + 1), dp = dq + (3 - (j & 1)) * (PANEL >> 4);
            wgmma_fence();
#pragma unroll
            for (int kk = 0; kk < 4; kk++) {
              wgmma_n112<1>(acc[0], dv + kk * 128, dp + kk * 2, kk > 0 ? 1 : j > 1);
              wgmma_n112<1>(acc[1], dv + 512 + kk * 128, dp + kk * 2, kk > 0 ? 1 : j > 1);
            }
          }
          wgmma_commit();
          bar_arrive(2 - wg, 256);
          wgmma_wait<1>();
          fence_regs(s);
          release(it);
          softmax(j & 1, 2 * j + 192);
          wgmma_wait<0>();
          fence_regs(acc[0]);
          fence_regs(acc[1]);
          release(it + 1);
          it += 2;
          if (!ok) {
            wait_full(it);
          }
        }
        it += 1;
        fence_async_smem();
        bar_sync(1 + wg, 256);
        wgmma_fence();
        issue_slab(da, dq + 3 * (PANEL >> 4), 1, IntC<1>{}, IntC<0>{});
        pin_order(never, 182);
        mbar_arrive1_if(empty0 + 8 * (NSLOT + 4 * wg + (tq >> 1)), tq < 4);
        rel = pick(tq == 0, empty0 + 8 * ring_slot(it - 1), pick(tq < 3, empty0 + 8 * (NSLOT + 4 * wg + 3), 0));
        next_unit(defer);
#pragma unroll
        for (int g = 0; g < 14; g++) asm volatile("add.rn.bf16x2 %0, %0, %1;" : "+r"(ps[g]) : "r"(pack_bf16(l[2 * g], l[2 * g + 1])));
        step_sums();
        wgmma_wait<1>();
        fence_regs(acc[0]);
        pack_half<0>(s, acc[0]);
        fence_half<0>(s);
        wgmma_wait_pin<0>(never, 172);
        fence_regs(acc[1]);
        mbar_arrive1_if(rel, rel);
        pack_half<1>(s, acc[1]);
        pend = 1;
      } else {
        turn(1, IntC<1>{}, IntC<1>{}, BoolC<false>{});
        pin_order(never, 186);
        it += nslab + 2 * (2 + (nslab - 6) / 5);
        peek();
        next_unit(defer);
        rel = pick(tq == 0, empty0 + 8 * ring_slot(wi), pick(tq < 3 && pos < 3, xbar + 8 * NBAR, 0));
        wgmma_wait<1>();
        fence_regs(acc[0]);
        pack_half<0>(s, acc[0]);
        fence_half<0>(s);
        wgmma_wait_pin<0>(never, 174);
        fence_regs(acc[1]);
        mbar_arrive1_if(rel, rel);
        pack_half<1>(s, acc[1]);
        pend = 2;
      }
      if (!defer) {
        mbar_wait_warp(ok_bar, uph);
        bar_sync(3 + wg, 128);
        if (pend == 2) {
          store_half<0>(st_p, s);
          store_half<1>(st_p, s);
        } else {
          rows_load(f, rows_addr());
          step_finite(f);
          step_rows(f, true);
          bar_sync(3 + wg, 128);
          free_panel(2);
          step_scales(f);
          if (__any_sync(0xffffffffu, read_verdict())) {
            step_redo(code);
          } else {
            f.dst = o_base(code) + warp * 3584 + lane * 4;
            step_write(f, 0, 56);
          }
        }
        step_signal(0);
        mbar_arrive1_if(sfull0 + 8 * (2 + wg), lane == 0);
        pend = 0;
#pragma unroll
        for (int i = 0; i < 14; i++) ps[i] = 0;
        if (left > 1) {
          wait_full(it + 1);
          wait_full(it + 2 * wg);
        }
      }
      prev = code, code = nxt, uph ^= 1;
    }
    if (wg == 0) bar_sync(1, 256);
  }
}

typedef CUresult (*EncodeFn)(CUtensorMap*, CUtensorMapDataType, cuuint32_t, void*, const cuuint64_t*, const cuuint64_t*,
                             const cuuint32_t*, const cuuint32_t*, CUtensorMapInterleave, CUtensorMapSwizzle,
                             CUtensorMapL2promotion, CUtensorMapFloatOOBfill);

bool encode(EncodeFn fn, CUtensorMap* m, const void* ptr, int rank, const cuuint64_t* dims, const cuuint64_t* strides,
            const cuuint32_t* box, CUtensorMapL2promotion promo, CUtensorMapSwizzle swz = CU_TENSOR_MAP_SWIZZLE_128B) {
  const cuuint32_t es[3] = {1, 1, 1};
  return fn(m, CU_TENSOR_MAP_DATA_TYPE_BFLOAT16, rank, const_cast<void*>(ptr), dims, strides, box, es,
            CU_TENSOR_MAP_INTERLEAVE_NONE, swz, promo,
            CU_TENSOR_MAP_FLOAT_OOB_FILL_NONE) == CUDA_SUCCESS;
}
bool encode_panels(EncodeFn fn, CUtensorMap* m, const void* ptr, uint64_t rows, uint64_t cols, uint32_t box_rows,
                   uint32_t box_blocks = 2) {
  const cuuint64_t dims[3] = {64, rows, cols / 64};
  const cuuint64_t strides[2] = {cols * 2, 128};
  const cuuint32_t box[3] = {64, box_rows, box_blocks};
  CUtensorMapL2promotion promo = CU_TENSOR_MAP_L2_PROMOTION_L2_128B;
  return encode(fn, m, ptr, 3, dims, strides, box, promo);
}
bool encode_2d(EncodeFn fn, CUtensorMap* m, const void* ptr, uint64_t rows, uint64_t cols, uint32_t box_rows,
               CUtensorMapSwizzle swz = CU_TENSOR_MAP_SWIZZLE_128B) {
  const cuuint64_t dims[2] = {cols, rows};
  const cuuint64_t strides[1] = {cols * 2};
  const cuuint32_t box[2] = {64, box_rows};
  CUtensorMapL2promotion promo = CU_TENSOR_MAP_L2_PROMOTION_L2_128B;
  return encode(fn, m, ptr, 2, dims, strides, box, promo, swz);
}

constexpr int kTunedPairs = 66;
const uint16_t kTunedBlock[kAttnUnits] = {
    20480, 20486, 20492, 20498, 20504, 16414, 16420, 16426, 16432, 16438, 16444, 16450, 16456, 16462, 16468, 20994,
    20481, 20487, 20493, 20499, 20505, 16415, 16421, 16427, 16433, 16439, 16445, 16451, 16457, 16463, 16469, 20995,
    20482, 20488, 20494, 20500, 20506, 16416, 16422, 16428, 16434, 16440, 16446, 16452, 16458, 16464, 16470, 20996,
    20483, 20489, 20495, 20501, 20507, 16417, 16423, 16429, 16435, 16441, 16447, 16453, 16459, 16465, 16471, 20997,
    20484, 20490, 20496, 20502, 16412, 16418, 16424, 16430, 16436, 16442, 16448, 16454, 16460, 16466, 20992, 20998,
    20485, 20491, 20497, 20503, 16413, 16419, 16425, 16431, 16437, 16443, 16449, 16455, 16461, 16467, 20993, 20999,
    21000, 21004, 21008, 21012, 21016, 16924, 16928, 16932, 16936, 16940, 16944, 16948, 16952, 16956, 16960, 16964,
    21001, 21005, 21009, 21013, 21017, 16925, 16929, 16933, 16937, 16941, 16945, 16949, 16953, 16957, 16961, 16965,
    21002, 21006, 21010, 21014, 21018, 16926, 16930, 16934, 16938, 16942, 16946, 16950, 16954, 16958, 16962, 16966,
    21003, 21007, 21011, 21015, 21019, 16927, 16931, 16935, 16939, 16943, 16947, 16951, 16955, 16959, 16963, 16967,
    16968, 16972, 16976, 16980, 21504, 21508, 21512, 21516, 21520, 21524, 21528, 17436, 17440, 17444, 17448, 17452,
    16969, 16973, 16977, 16981, 21505, 21509, 21513, 21517, 21521, 21525, 21529, 17437, 17441, 17445, 17449, 17453,
    16970, 16974, 16978, 16982, 21506, 21510, 21514, 21518, 21522, 21526, 21530, 17438, 17442, 17446, 17450, 17454,
    16971, 16975, 16979, 16983, 21507, 21511, 21515, 21519, 21523, 21527, 21531, 17439, 17443, 17447, 17451, 17455,
    17456, 17460, 17464, 17468, 17472, 17476, 17480, 17484, 17488, 17492, 22016, 22020, 22024, 22028, 22032, 22036,
    17457, 17461, 17465, 17469, 17473, 17477, 17481, 17485, 17489, 17493, 22017, 22021, 22025, 22029, 22033, 22037,
    17458, 17462, 17466, 17470, 17474, 17478, 17482, 17486, 17490, 17494, 22018, 22022, 22026, 22030, 22034, 22038,
    17459, 17463, 17467, 17471, 17475, 17479, 17483, 17487, 17491, 17495, 22019, 22023, 22027, 22031, 22035, 22039,
    22040, 22041, 22042, 22043, 17948, 17949, 17950, 17951, 17952, 17953, 17954, 17955, 17956, 17957, 17958, 17959,
    17960, 17961, 17962, 17963, 17964, 17965, 17966, 17967, 17968, 17969, 17970, 17971, 17972, 17973, 17974, 17975,
    17976, 17978, 17980, 17982, 17984, 17986, 17988, 17990, 17992, 17994, 17996, 17998, 18000, 18002, 18004, 18006,
    17977, 17979, 17981, 17983, 17985, 17987, 17989, 17991, 17993, 17995, 17997, 17999, 18001, 18003, 18005, 18007,
    22528, 22538, 22548, 4186, 4196, 4206, 4216, 4226, 4236, 4246, 4256, 4266, 4276, 4286, 4296, 4306,
    22529, 22539, 22549, 4187, 4197, 4207, 4217, 4227, 4237, 4247, 4257, 4267, 4277, 4287, 4297, 4307,
    22530, 22540, 22550, 4188, 4198, 4208, 4218, 4228, 4238, 4248, 4258, 4268, 4278, 4288, 4298, 4308,
    22531, 22541, 22551, 4189, 4199, 4209, 4219, 4229, 4239, 4249, 4259, 4269, 4279, 4289, 4299, 4309,
    22532, 22542, 22552, 4190, 4200, 4210, 4220, 4230, 4240, 4250, 4260, 4270, 4280, 4290, 4300, 4310,
    22533, 22543, 22553, 4191, 4201, 4211, 4221, 4231, 4241, 4251, 4261, 4271, 4281, 4291, 4301, 4311,
    22534, 22544, 22554, 4192, 4202, 4212, 4222, 4232, 4242, 4252, 4262, 4272, 4282, 4292, 4302, 4312,
    22535, 22545, 22555, 4193, 4203, 4213, 4223, 4233, 4243, 4253, 4263, 4273, 4283, 4293, 4303, 4313,
    22536, 22546, 4184, 4194, 4204, 4214, 4224, 4234, 4244, 4254, 4264, 4274, 4284, 4294, 4304, 4314,
    22537, 22547, 4185, 4195, 4205, 4215, 4225, 4235, 4245, 4255, 4265, 4275, 4285, 4295, 4305, 4315};
const uint8_t kTunedLen[kTunedPairs] = {
    9, 9, 9, 8, 10, 9, 9, 10, 9, 9, 10, 9, 10, 10, 10, 10, 10, 11, 10, 11, 9, 10, 10, 10, 11, 9, 10, 11, 10, 9, 11, 9, 10,
    10, 9, 9, 10, 10, 10, 9, 10, 9, 11, 10, 10, 10, 10, 10, 10, 10, 12, 10, 9, 9, 10, 11, 11, 10, 9, 11, 10, 10, 10, 10, 9, 9};
const uint8_t kTunedDelay[kTunedPairs] = {
    89, 0, 27, 0, 0, 113, 0, 50, 0, 1, 78, 9, 0, 7, 0, 0, 0, 0, 0, 0, 0, 0,
    0, 0, 0, 0, 0, 0, 17, 111, 0, 0, 0, 0, 0, 5, 0, 5, 0, 0, 17, 105, 3, 0,
    0, 0, 1, 0, 11, 0, 0, 0, 0, 0, 1, 0, 0, 7, 0, 7, 0, 0, 27, 0, 115, 107};
const uint16_t kTunedUnit[] = {
    16394, 36111, 24796, 45325, 320, 418, 472, 494, 64223, 66, 34063, 16579, 43531, 294, 334, 437, 25083, 58376,
    57, 35087, 196, 258, 293, 333, 405, 16843, 55919, 65, 33807, 179, 257, 291, 16731, 51727, 59919, 21,
    46, 16491, 35023, 190, 281, 316, 370, 25016, 63501, 74, 102, 212, 274, 16674, 50447, 408, 25022, 63748,
    36, 61, 16537, 40207, 267, 340, 419, 473, 431, 16457, 34827, 209, 223, 16653, 47625, 450, 504, 383,
    58079, 35, 33295, 211, 273, 16671, 50191, 376, 16798, 54719, 55, 97, 110, 16570, 44303, 339, 403, 457,
    415, 89, 116, 193, 207, 253, 341, 451, 505, 447, 57839, 72, 146, 159, 16556, 45583, 342, 372,
    426, 511, 33, 27, 150, 16581, 46087, 239, 345, 468, 16747, 62047, 40, 114, 24703, 40971, 232, 310,
    401, 439, 16877, 56495, 64, 37381, 117, 210, 225, 255, 346, 500, 24971, 56329, 83, 13, 105, 167,
    276, 298, 368, 358, 25004, 55303, 0, 32771, 132, 162, 224, 285, 327, 388, 25018, 64012, 82, 16412,
    37183, 189, 16617, 43727, 16727, 47791, 407, 16861, 60847, 54, 79, 156, 201, 246, 301, 416, 406, 25052,
    64519, 2, 59, 16503, 35535, 174, 265, 16702, 48607, 420, 25050, 62474, 53, 78, 139, 16553, 44047, 323,
    371, 16825, 61487, 17, 11, 16518, 41484, 264, 313, 449, 487, 16766, 52671, 68, 93, 122, 168, 245,
    299, 384, 374, 16828, 56719, 32, 35339, 192, 206, 234, 317, 386, 456, 478, 59871, 67, 16476, 32847,
    16588, 39391, 16666, 47439, 467, 362, 463, 61935, 7, 112, 16509, 42255, 268, 325, 435, 25065, 57356, 50,
    12, 104, 182, 228, 297, 352, 501, 24988, 53767, 22, 47, 16508, 36063, 221, 249, 315, 354, 424,
    16846, 62655, 9, 16499, 37487, 16571, 46345, 296, 335, 469, 24956, 64775, 58, 149, 164, 226, 288, 331,
    357, 24987, 60681, 1, 37122, 100, 161, 175, 16650, 46511, 351, 485, 16780, 53903, 20, 45, 137, 16583,
    43023, 338, 355, 25001, 57868, 16, 38148, 148, 178, 256, 270, 344, 436, 25066, 52490, 19, 60, 24712,
    39180, 280, 312, 433, 471, 16750, 51375, 70, 95, 16493, 41999, 252, 322, 498, 16777, 59439, 8, 145,
    158, 171, 16647, 48143, 356, 410, 495, 85, 16399, 37999, 181, 243, 295, 350, 453, 24940, 53256, 87,
    129, 142, 218, 247, 307, 353, 502, 16797, 55711, 5, 30, 154, 200, 16661, 46223, 330, 484, 16763,
    54367, 48, 33039, 163, 241, 16655, 49551, 499, 24970, 59660, 25, 35852, 177, 191, 16668, 49415, 465, 503,
    61441, 399, 26, 101, 194, 272, 286, 329, 452, 16890, 63839, 71, 113, 126, 202, 16615, 43471, 319,
    16786, 54538, 53512, 62723, 38, 63, 140, 16569, 40095, 254, 328, 404, 16842, 62799, 81, 37893, 16517, 39944,
    240, 16622, 49167, 375, 25021, 55813, 37, 62, 123, 216, 230, 300, 400, 390, 25036, 56583, 23, 128,
    141, 217, 262, 306, 496, 486, 16781, 53663, 52, 77, 106, 16599, 43275, 309, 385, 391, 25037, 60421,
    88, 99, 160, 188, 279, 308, 369, 359, 16813, 58527, 51, 76, 152, 214, 260, 304, 464, 454,
    16749, 53407, 86, 16480, 36927, 16589, 41695, 237, 16708, 51462, 16807, 52226, 367, 57567, 34, 91, 151, 166,
    275, 48396, 497, 392, 25006, 61956, 6, 31, 16492, 41231, 236, 337, 482, 24953, 61709, 49, 43, 16487,
    38927, 251, 321, 466, 24937, 57613, 39, 144, 157, 170, 278, 302, 432, 422, 16876, 64911, 80, 36866,
    147, 208, 222, 16634, 47363, 332, 373, 25003, 58633, 4, 29, 121, 183, 229, 45551, 314, 481, 360,
    24974, 54276, 24, 98, 111, 16587, 45071, 326, 483, 378, 479, 63727, 3, 44, 120, 198, 16628, 47119,
    387, 16793, 52287, 56, 130, 143, 16603, 41167, 235, 336, 434, 488, 8702, 59393, 18, 75, 135, 213,
    259, 303, 448, 438, 16892, 55439, 69, 94, 16539, 39439, 16667, 49667, 349, 421, 16875, 51583, 41, 131,
    176, 173, 248, 311, 417, 455, 16893, 58799, 84, 14, 138, 184, 261, 305, 480, 470, 16765, 64655,
    90, 118, 165, 227, 292, 348, 389, 16827, 60527, 16426, 38239, 180, 242, 16673, 49743, 51209, 25051, 55560};
void build_schedule(Params& prm, int pairs) {
  for (int i = 0; i < kAttnUnits; i++) prm.blk[i] = (uint16_t)(i | 1 << 12);
  uint8_t delay[kMaxPairs] = {};
  static uint16_t lists[kMaxPairs][kMaxUnits];
  int n[kMaxPairs] = {};
  double t[kMaxPairs] = {};
  const double ta = 40.0, to = 59.0;
  for (int u = 0; u < kUnits; u++) {
    int p = 0;
    for (int q = 1; q < pairs; q++)
      if (t[q] < t[p] - 1e-9) p = q;
    uint16_t code;
    if (u < kAttnUnits) {
      code = (uint16_t)u;
    } else {
      const int o = u - kAttnUnits, g2 = o / 5, r = o % 5;
      code = (uint16_t)(0x800F | (r < 4 ? ((2 * g2 + (r >> 1)) << 2) | (r & 1) : ((2 * g2) << 2) | 2) << 8);
    }
    lists[p][n[p]++] = code;
    t[p] += u < kAttnUnits ? ta : to;
  }
  if (pairs == kTunedPairs) {
    for (int p = 0, o = 0; p < pairs; p++) {
      n[p] = kTunedLen[p];
      delay[p] = kTunedDelay[p];
      for (int i = 0; i < n[p]; i++) lists[p][i] = kTunedUnit[o++];
    }
    for (int i = 0; i < kAttnUnits; i++) prm.blk[i] = kTunedBlock[i];
  }
  int o = 0;
  for (int p = 0; p < pairs; p++) {
    prm.head[p] = o | n[p] << 10 | delay[p] << 15 | (uint32_t)(lists[p][0] & 511) << 23;
    for (int i = 0; i < n[p]; i++) prm.unit[o++] = lists[p][i];
  }
}

}

extern "C" void kernel_launch(void* const* d_in, const int* in_sizes, int n_in, void* d_out, int out_size) {
  (void)in_sizes; (void)n_in; (void)out_size;
  void* fnp = nullptr;
  cudaDriverEntryPointQueryResult qr;
  if (cudaGetDriverEntryPoint("cuTensorMapEncodeTiled", &fnp, cudaEnableDefault, &qr) != cudaSuccess || !fnp) return;
  EncodeFn fn = (EncodeFn)fnp;
  void* optr = nullptr;
  cudaGetSymbolAddress(&optr, g_o);
  Params prm;
  bool ok = true;
  for (int br = 0; br < 2; br++) {
    void* const* in = d_in + 5 * br;
    ok &= encode_2d(fn, &prm.x[br], in[0], (uint64_t)kB * kSq, kD, NQ);
    ok &= encode_panels(fn, &prm.kv[br], in[1], (uint64_t)kB * kH * kSk, kDh, 64);
    ok &= encode_panels(fn, &prm.kv[2 + br], in[2], (uint64_t)kB * kH * kSk, kDh, 64);
    ok &= encode_panels(fn, &prm.wq[br], in[3], kD, kH * kDh, 64);
    ok &= encode_panels(fn, &prm.wo[br], in[4], kH * kDh, kD, 64);
    prm.xp[br] = (const __nv_bfloat16*)in[0];
    prm.wp[br] = (const __nv_bfloat16*)in[3];
    prm.kp[br] = (const __nv_bfloat16*)in[1];
    prm.vp[br] = (const __nv_bfloat16*)in[2];
  }
  prm.op = (__nv_bfloat16*)d_out;
  ok &= encode_2d(fn, &prm.o_ld, optr, (uint64_t)kAttnUnits * 4 * kSq, 64, NQ, CU_TENSOR_MAP_SWIZZLE_NONE);
  ok &= encode_panels(fn, &prm.out, d_out, (uint64_t)kB * kSq, 2 * kD, ST_ROWS, 1);
  if (!ok) return;
  cudaFuncSetAttribute(mha_fused_kernel, cudaFuncAttributeMaxDynamicSharedMemorySize, SMEM_BYTES);
  cudaLaunchConfig_t cfg = {};
  cfg.gridDim = dim3(2);
  cfg.blockDim = dim3(384);
  cfg.dynamicSmemBytes = SMEM_BYTES;
  cfg.stream = cudaStreamPerThread;
  int pairs = 0;
  if (cudaOccupancyMaxActiveClusters(&pairs, mha_fused_kernel, &cfg) != cudaSuccess || pairs < 1) return;
  if (pairs > kMaxPairs) pairs = kMaxPairs;
  if (pairs < 24) return;
  build_schedule(prm, pairs);
  mha_fused_kernel<<<2 * pairs, 384, SMEM_BYTES, cudaStreamPerThread>>>(prm);
}
```

```cpp
#include <cuda_runtime.h>
#include <cuda_bf16.h>
#include <cuda.h>
#include <stdint.h>

namespace {

constexpr int kB = 16, kSq = 224, kD = 640, kH = 32, kSk = 1024, kDh = 128;
constexpr int kGroups = 2 * kB;
constexpr int kAttnUnits = kGroups * kH / 2;
constexpr int kOutUnits = kGroups * 5 / 2;
constexpr int kUnits = kAttnUnits + kOutUnits;
constexpr int kMaxUnits = kUnits + 64;
constexpr int kMaxPairs = 72;
constexpr int NQ = 112;
constexpr int PANEL = NQ * 128;
constexpr float kQScale = 0.08838834764831845f * 1.4426950408889634f;
constexpr int SLOT = 16384;
constexpr int NSLOT = 7;

constexpr int SM_PANEL = 0;
constexpr int SM_RING = SM_PANEL + 8 * PANEL;
constexpr int NBAR = NSLOT + 8;
constexpr int SM_RCP = SM_RING + NSLOT * SLOT;
constexpr int SM_BAR = SM_RCP + 640;
constexpr int SM_END = SM_BAR + 8 * (2 * NBAR + 12) + 32;
constexpr int SMEM_BYTES = SM_END + 1024;
static_assert(SM_RING % 1024 == 0 && PANEL % 1024 == 0, "swizzle alignment");
static_assert(SMEM_BYTES <= 232448, "smem");

struct Params {
  CUtensorMap x[2], wq[2], kv[4], wo[2];
  CUtensorMap o_ld, out;
  const __nv_bfloat16* xp[2];
  const __nv_bfloat16* wp[2];
  const __nv_bfloat16* kp[2];
  const __nv_bfloat16* vp[2];
  __nv_bfloat16* op;
  uint32_t head[kMaxPairs];
  uint16_t unit[kMaxUnits];
  uint16_t blk[kAttnUnits];
};

struct Unit {
  bool attn, mc;
  int g, hc;
  int h0, nslab;
};
__device__ __forceinline__ int unit_slabs(uint32_t u) {
  return (u & 0x8000u) ? 4 * ((u & 15) + 1 - ((u >> 4) & 15)) : kD / 64;
}
__device__ __forceinline__ Unit decode_unit(uint32_t u, uint32_t rank) {
  Unit r;
  r.attn = !(u & 0x8000u);
  r.nslab = unit_slabs(u);
  if (r.attn) {
    r.g = (u >> 4) & 31;
    r.hc = (u & 15) * 2 + rank;
    r.mc = true;
    r.h0 = 0;
  } else {
    const uint32_t t = (u >> 8) & 3;
    r.mc = t < 2;
    r.g = ((u >> 10) & 31) + (t < 2 ? 0 : rank);
    r.hc = t < 2 ? 2 * t + rank : 4;
    r.h0 = (u >> 4) & 15;
  }
  return r;
}

__device__ uint4 g_qrow[2 * kMaxPairs * 2 * 16 * 128];
__device__ unsigned int g_pc[128 * 16 * 2];
__device__ __nv_bfloat16 g_o[(size_t)kAttnUnits * kSq * 2 * kDh];
__device__ unsigned int g_ticket;
__device__ unsigned int g_rd[kAttnUnits];
__device__ unsigned int g_cnt[kAttnUnits];

constexpr int CREGS = 232, SM_OFF = -2, Q_PIN = 0x15, ST_ROWS = 56;
template <bool V>
struct BoolC {
  static constexpr bool value = V;
};
template <int V>
struct IntC {
  static constexpr int value = V;
};
template <int I, int N, class F>
__device__ __forceinline__ void static_for(F&& f) {
  if constexpr (I < N) {
    f(IntC<I>{});
    static_for<I + 1, N>(f);
  }
}
constexpr uint32_t kPat0 = 04321432100, kPat1 = 04302102100;
__host__ __device__ constexpr int x_pos(int pat, int k) { return ((pat == 0 ? kPat0 : kPat1) >> 3 * k) & 7; }
__host__ __device__ constexpr int x_off(int pat, int k) { return k == 0 ? 0 : x_off(pat, k - 1) + (x_pos(pat, k - 1) == 0 ? 3 : 1); }
__host__ __device__ constexpr int w_cut(int i) { return 56 * i / 5; }
__device__ __forceinline__ uint32_t unit_pattern(uint32_t u, uint32_t prev) {
  return !(u & 0x8000u) && (prev & 0x8000u) ? kPat1 : kPat0;
}
__device__ __forceinline__ uint32_t next_pos(uint32_t pos, int k, uint32_t pat) {
  return k < 9 ? (pat >> (3 * k + 3)) & 7 : pos == 4 ? 0 : pos + 1;
}
__device__ __forceinline__ uint32_t pick(bool c, uint32_t a, uint32_t b) {
  uint32_t r;
  asm("{\n.reg .pred p;\nsetp.ne.u32 p, %1, 0;\nselp.u32 %0, %2, %3, p;\n}" : "=r"(r) : "r"((uint32_t)c), "r"(a), "r"(b));
  return r;
}
__device__ __forceinline__ uint32_t ring_round(uint32_t i) { return (i * 9363u) >> 16; }
__device__ __forceinline__ uint32_t ring_slot(uint32_t i) { return i - NSLOT * ring_round(i); }
__device__ __forceinline__ uint32_t ring_par(uint32_t i) { return ring_round(i) & 1; }

__device__ __forceinline__ uint32_t smem_u32(const void* p) { return (uint32_t)__cvta_generic_to_shared(p); }
__device__ __forceinline__ void mbar_init(uint32_t bar, uint32_t cnt) {
  asm volatile("mbarrier.init.shared::cta.b64 [%0], %1;" ::"r"(bar), "r"(cnt));
}
__device__ __forceinline__ void mbar_arrive1_if(uint32_t bar, bool pred) {
  asm volatile("{\n.reg .pred p;\nsetp.ne.u32 p, %1, 0;\n@p mbarrier.arrive.shared::cta.b64 _, [%0];\n}" ::"r"(bar), "r"((uint32_t)pred)
               : "memory");
}
__device__ __forceinline__ void mbar_wait_warp(uint32_t bar, uint32_t parity) {
  asm volatile(
      "{\n.reg .pred p, q;\n.reg .u32 c;\n"
      "mov.u32 c, 0;\n"
      "SPIN:\n"
      "mbarrier.try_wait.parity.shared::cta.b64 p, [%0], %1;\n"
      "vote.sync.all.pred q, p, 0xffffffff;\n"
      "@q bra.uni DONE;\n"
      "add.u32 c, c, 1;\n"
      "setp.gt.u32 q, c, 0x1000000;\n"
      "@q trap;\n"
      "bra.uni SPIN;\n"
      "DONE:\n}" ::"r"(bar),
      "r"(parity)
      : "memory");
}
__device__ __forceinline__ uint32_t mbar_test(uint32_t bar, uint32_t parity) {
  uint32_t ok;
  asm volatile(
      "{\n.reg .pred p;\nmbarrier.test_wait.parity.shared::cta.b64 p, [%1], %2;\nselp.u32 %0, 1, 0, p;\n}"
      : "=r"(ok)
      : "r"(bar), "r"(parity)
      : "memory");
  return ok;
}
__device__ __forceinline__ uint32_t mbar_test_if(uint32_t bar, uint32_t parity, bool pred) {
  uint32_t ok;
  asm volatile(
      "{\n.reg .pred p, q;\nsetp.ne.u32 q, %3, 0;\nsetp.eq.u32 p, %3, 0;\n"
      "@q mbarrier.test_wait.parity.shared::cta.b64 p, [%1], %2;\nselp.u32 %0, 1, 0, p;\n}"
      : "=r"(ok)
      : "r"(bar), "r"(parity), "r"((uint32_t)pred)
      : "memory");
  return ok;
}
#define ELECTED "{\n.reg .pred e;\nelect.sync _|e, 0xffffffff;\n@e "
constexpr uint64_t kEvictFirst = 0x12F0000000000000ull, kEvictNormal = 0x1000000000000000ull;
__device__ __forceinline__ void flag_wait(const unsigned int* p, uint32_t target) {
  asm volatile(
      "{\n.reg .pred p, q;\n.reg .u32 c, v;\n"
      "mov.u32 c, 0;\n"
      "SPIN:\n"
      "ld.acquire.gpu.global.u32 v, [%0];\n"
      "setp.ge.u32 p, v, %1;\n"
      "vote.sync.all.pred q, p, 0xffffffff;\n"
      "@q bra.uni DONE;\n"
      "nanosleep.u32 200;\n"
      "add.u32 c, c, 1;\n"
      "setp.gt.u32 q, c, 0x1000000;\n"
      "@q trap;\n"
      "bra.uni SPIN;\n"
      "DONE:\n}" ::"l"(p),
      "r"(target)
      : "memory");
}
__device__ __forceinline__ uint32_t flags_wait(const unsigned int* p, uint32_t target, uint32_t need) {
  uint32_t m;
  asm volatile(
      "{\n.reg .pred p, q;\n.reg .u32 c, v;\n"
      "mov.u32 c, 0;\n"
      "SPIN:\n"
      "ld.acquire.gpu.global.u32 v, [%1];\n"
      "setp.ge.u32 p, v, %2;\n"
      "vote.sync.ballot.b32 %0, p, 0xffffffff;\n"
      "and.b32 v, %0, %3;\n"
      "setp.eq.u32 q, v, %3;\n"
      "@q bra.uni DONE;\n"
      "add.u32 c, c, 1;\n"
      "setp.gt.u32 q, c, 0x1000000;\n"
      "@q trap;\n"
      "bra.uni SPIN;\n"
      "DONE:\n"
      "fence.proxy.async.global;\n}"
      : "=&r"(m)
      : "l"(p), "r"(target), "r"(need)
      : "memory");
  return m;
}
__device__ __forceinline__ void e_arrive(uint32_t bar, uint32_t n) {
  asm volatile(ELECTED "mbarrier.arrive.shared::cta.b64 _, [%0], %1;\n}" ::"r"(bar), "r"(n) : "memory");
}
__device__ __forceinline__ void e_expect_tx(uint32_t bar, uint32_t bytes) {
  asm volatile(ELECTED "mbarrier.arrive.expect_tx.shared::cta.b64 _, [%0], %1;\n}" ::"r"(bar), "r"(bytes) : "memory");
}
__device__ __forceinline__ void tma_ld2(uint32_t dst, const CUtensorMap* m, int c0, int c1, uint32_t bar, uint64_t pol) {
  asm volatile(ELECTED
               "cp.async.bulk.tensor.2d.shared::cluster.global.mbarrier::complete_tx::bytes.L2::cache_hint [%0], [%1, {%3, %4}], "
               "[%2], %5;\n}" ::"r"(dst),
               "l"(m), "r"(bar), "r"(c0), "r"(c1), "l"(pol)
               : "memory");
}
__device__ __forceinline__ void tma_ld2_mc(uint32_t dst, const CUtensorMap* m, int c0, int c1, uint32_t bar, uint64_t pol) {
  asm volatile(ELECTED
               "cp.async.bulk.tensor.2d.shared::cluster.global.mbarrier::complete_tx::bytes.multicast::cluster.L2::cache_hint "
               "[%0], [%1, {%3, %4}], [%2], %5, %6;\n}" ::"r"(dst),
               "l"(m), "r"(bar), "r"(c0), "r"(c1), "h"((uint16_t)3), "l"(pol)
               : "memory");
}
__device__ __forceinline__ void tma_ld3(uint32_t dst, const CUtensorMap* m, int c1, int c2, uint32_t bar, uint64_t pol) {
  asm volatile(ELECTED
               "cp.async.bulk.tensor.3d.shared::cluster.global.mbarrier::complete_tx::bytes.L2::cache_hint [%0], [%1, {%3, %4, "
               "%5}], [%2], %6;\n}" ::"r"(dst),
               "l"(m), "r"(bar), "r"(0), "r"(c1), "r"(c2), "l"(pol)
               : "memory");
}
__device__ __forceinline__ void tma_ld4(uint32_t dst, const CUtensorMap* m, int c3, uint32_t bar, uint64_t pol) {
  asm volatile(ELECTED
               "cp.async.bulk.tensor.4d.shared::cluster.global.mbarrier::complete_tx::bytes.L2::cache_hint [%0], [%1, {%3, %3, "
               "%3, %4}], [%2], %5;\n}" ::"r"(dst),
               "l"(m), "r"(bar), "r"(0), "r"(c3), "l"(pol)
               : "memory");
}
__device__ __forceinline__ void tma_st3(const CUtensorMap* m, int c1, int c2, uint32_t src, bool add) {
  if (add)
    asm volatile(ELECTED "cp.reduce.async.bulk.tensor.3d.global.shared::cta.add.bulk_group [%0, {%2, %3, %4}], [%1];\n}" ::"l"(m), "r"(src),
                 "r"(0), "r"(c1), "r"(c2)
                 : "memory");
  else
    asm volatile(ELECTED "cp.async.bulk.tensor.3d.global.shared::cta.bulk_group [%0, {%2, %3, %4}], [%1];\n}" ::"l"(m), "r"(src), "r"(0),
                 "r"(c1), "r"(c2)
                 : "memory");
}
__device__ __forceinline__ void wgmma_fence() { asm volatile("wgmma.fence.sync.aligned;" ::: "memory"); }
__device__ __forceinline__ void wgmma_commit() { asm volatile("wgmma.commit_group.sync.aligned;" ::: "memory"); }
template <int N>
__device__ __forceinline__ void wgmma_wait() {
  asm volatile("wgmma.wait_group.sync.aligned %0;" ::"n"(N) : "memory");
}
template <int N>
__device__ __forceinline__ void wgmma_wait_pin(int never, int c) {
  asm volatile("{\n.reg .pred p;\nsetp.eq.u32 p, %1, %2;\nAGAIN:\nwgmma.wait_group.sync.aligned %0;\n@p bra.uni AGAIN;\n}" ::"n"(N),
               "r"(never), "r"(c)
               : "memory");
}
__device__ __forceinline__ void pin_order(int never, int c) {
  asm volatile("{\n.reg .pred p;\nsetp.eq.u32 p, %0, %1;\nAGAIN:\n@p nanosleep.u32 1;\n@p bra.uni AGAIN;\n}" ::"r"(never), "r"(c) : "memory");
}
template <int N>
__device__ __forceinline__ void fence_regs(float (&d)[N]) {
#pragma unroll
  for (int i = 0; i < N; i++) asm volatile("" : "+f"(d[i])::"memory");
}
__device__ __forceinline__ void fence_async_smem() { asm volatile("fence.proxy.async.shared::cta;" ::: "memory"); }
__device__ __forceinline__ void bar_sync(int id, int n) { asm volatile("bar.sync %0, %1;" ::"r"(id), "r"(n) : "memory"); }
__device__ __forceinline__ void bar_arrive(int id, int n) {
  asm volatile("bar.arrive %0, %1;" ::"r"(id), "r"(n) : "memory");
}
__device__ __forceinline__ void stsm_x4_t(uint32_t addr, uint32_t r0, uint32_t r1, uint32_t r2, uint32_t r3) {
  asm volatile("stmatrix.sync.aligned.m8n8.x4.trans.shared.b16 [%0], {%1, %2, %3, %4};" ::"r"(addr), "r"(r0), "r"(r1),
               "r"(r2), "r"(r3)
               : "memory");
}
__device__ __forceinline__ void stsm_x4_t_pin(uint32_t addr, uint32_t r0, uint32_t r1, uint32_t r2, uint32_t r3, int never, int c) {
  asm volatile(
      "{\n.reg .pred p;\nsetp.eq.u32 p, %5, %6;\nAGAIN:\n"
      "stmatrix.sync.aligned.m8n8.x4.trans.shared.b16 [%0], {%1, %2, %3, %4};\n@p bra.uni AGAIN;\n}" ::"r"(addr),
      "r"(r0), "r"(r1), "r"(r2), "r"(r3), "r"(never), "r"(c)
      : "memory");
}
__device__ __forceinline__ uint32_t pack_bf16(float lo, float hi) {
  uint32_t r;
  asm("cvt.rn.bf16x2.f32 %0, %1, %2;" : "=r"(r) : "f"(hi), "f"(lo));
  return r;
}
__device__ __forceinline__ float ex2(float x) {
  float y;
  asm("ex2.approx.ftz.f32 %0, %1;" : "=f"(y) : "f"(x));
  return y;
}
__device__ __forceinline__ uint32_t mk_desc(uint32_t addr) { return (1u << 16) | ((addr & 0x3FFFFu) >> 4); }

template <int TA, int TB = 0, int KV = 0>
__device__ __forceinline__ void wgmma_n112(float (&d)[56], uint32_t descA, uint32_t descB, int scaleD) {
  asm volatile(
      "{\n.reg .pred p;\n.reg .b32 hi, hb;\n.reg .b64 da, db;\nsetp.ne.b32 p, %58, 0;\n"
      "mov.b32 hi, %62;\nmov.b32 hb, %61;\nmov.b64 da, {%56, hi};\nmov.b64 db, {%57, hb};\n"
      "wgmma.mma_async.sync.aligned.m64n112k16.f32.bf16.bf16 "
      "{%0, %1, %2, %3, %4, %5, %6, %7, %8, %9, %10, %11, %12, %13, "
      "%14, %15, %16, %17, %18, %19, %20, %21, %22, %23, %24, %25, %26, %27, "
      "%28, %29, %30, %31, %32, %33, %34, %35, %36, %37, %38, %39, %40, %41, "
      "%42, %43, %44, %45, %46, %47, %48, %49, %50, %51, %52, %53, %54, %55}, "
      "da, db, p, 1, 1, %59, %60;\n}\n"
      : "+f"(d[0]), "+f"(d[1]), "+f"(d[2]), "+f"(d[3]), "+f"(d[4]), "+f"(d[5]), "+f"(d[6]),
        "+f"(d[7]), "+f"(d[8]), "+f"(d[9]), "+f"(d[10]), "+f"(d[11]), "+f"(d[12]), "+f"(d[13]),
        "+f"(d[14]), "+f"(d[15]), "+f"(d[16]), "+f"(d[17]), "+f"(d[18]), "+f"(d[19]), "+f"(d[20]),
        "+f"(d[21]), "+f"(d[22]), "+f"(d[23]), "+f"(d[24]), "+f"(d[25]), "+f"(d[26]), "+f"(d[27]),
        "+f"(d[28]), "+f"(d[29]), "+f"(d[30]), "+f"(d[31]), "+f"(d[32]), "+f"(d[33]), "+f"(d[34]),
        "+f"(d[35]), "+f"(d[36]), "+f"(d[37]), "+f"(d[38]), "+f"(d[39]), "+f"(d[40]), "+f"(d[41]),
        "+f"(d[42]), "+f"(d[43]), "+f"(d[44]), "+f"(d[45]), "+f"(d[46]), "+f"(d[47]), "+f"(d[48]),
        "+f"(d[49]), "+f"(d[50]), "+f"(d[51]), "+f"(d[52]), "+f"(d[53]), "+f"(d[54]), "+f"(d[55])
      : "r"(descA), "r"(descB), "r"(scaleD), "n"(TA), "n"(TB), "n"(TB ? 8 : 0x40000040), "n"(KV ? 0x40000080 : 0x40000040));
}

template <int T>
__device__ __forceinline__ void pack_half(float (&pk)[56], const float (&a)[56]) {
#pragma unroll
  for (int i = 0; i < 28; i++) pk[28 * T + i] = __uint_as_float(pack_bf16(a[2 * i], a[2 * i + 1]));
}
template <int T>
__device__ __forceinline__ void fence_half(float (&pk)[56]) {
#pragma unroll
  for (int i = 0; i < 28; i++) asm volatile("" : "+f"(pk[28 * T + i])::"memory");
}
template <int T>
__device__ __forceinline__ void store_half(uint32_t addr, const float (&pk)[56]) {
#pragma unroll
  for (int q = 0; q < 7; q++) {
    const float* r = pk + 28 * T + 4 * q;
    stsm_x4_t(addr + T * PANEL + q * 2048, __float_as_uint(r[0]), __float_as_uint(r[1]), __float_as_uint(r[2]), __float_as_uint(r[3]));
  }
}

template <int T>
__device__ __forceinline__ void q_half(uint32_t addr, float (&pk)[56], const float (&a)[56], int never) {
#pragma unroll
  for (int q = 0; q < 7; q++) {
    uint32_t r[4];
#pragma unroll
    for (int i = 0; i < 4; i++) {
      r[i] = pack_bf16(a[8 * q + 2 * i] * kQScale, a[8 * q + 2 * i + 1] * kQScale);
      pk[28 * T + 4 * q + i] = __uint_as_float(r[i]);
    }
    if (q < 6 && (Q_PIN >> q & 1)) stsm_x4_t_pin(addr + T * PANEL + q * 2048, r[0], r[1], r[2], r[3], never, 32 + 2 * (7 * T + q));
    else stsm_x4_t(addr + T * PANEL + q * 2048, r[0], r[1], r[2], r[3]);
  }
}

__device__ __forceinline__ float bf_lo(uint32_t u) { return __uint_as_float(u << 16); }
__device__ __forceinline__ float bf_hi(uint32_t u) { return __uint_as_float(u & 0xFFFF0000u); }

__device__ __forceinline__ void fma8(float* o, float a, const uint4& w, float c) {
  o[0] = fmaf(a, bf_lo(w.x), o[0] * c), o[1] = fmaf(a, bf_hi(w.x), o[1] * c);
  o[2] = fmaf(a, bf_lo(w.y), o[2] * c), o[3] = fmaf(a, bf_hi(w.y), o[3] * c);
  o[4] = fmaf(a, bf_lo(w.z), o[4] * c), o[5] = fmaf(a, bf_hi(w.z), o[5] * c);
  o[6] = fmaf(a, bf_lo(w.w), o[6] * c), o[7] = fmaf(a, bf_hi(w.w), o[7] * c);
}
__device__ __forceinline__ void slow_rows(uint4* qrow, int tq, const __nv_bfloat16* xp, const __nv_bfloat16* wp,
                                          const __nv_bfloat16* kp, const __nv_bfloat16* vp, __nv_bfloat16* op) {
  if (tq >= NQ) return;
#pragma unroll 1
  for (int c = 0; c < 16; c++) {
    float q[8] = {};
#pragma unroll 1
    for (int k = 0; k < kD; k++)
      fma8(q, __bfloat162float(xp[tq * kD + k]), __ldg(reinterpret_cast<const uint4*>(wp + k * (kH * kDh)) + c), 1.f);
    qrow[c * 128] = make_uint4(pack_bf16(q[0] * kQScale, q[1] * kQScale), pack_bf16(q[2] * kQScale, q[3] * kQScale),
                               pack_bf16(q[4] * kQScale, q[5] * kQScale), pack_bf16(q[6] * kQScale, q[7] * kQScale));
  }
#pragma unroll 1
  for (int pass = 0; pass < 4; pass++) {
    float o[32] = {}, m = -INFINITY, l = 0.f;
#pragma unroll 1
    for (int key = 0; key < kSk; key++) {
      const uint4* kr = reinterpret_cast<const uint4*>(kp + key * kDh);
      const uint4* vr = reinterpret_cast<const uint4*>(vp + key * kDh) + 4 * pass;
      float s = 0.f;
#pragma unroll 1
      for (int c = 0; c < 16; c++) {
        const uint4 q = qrow[c * 128], k = __ldg(kr + c);
        s = fmaf(bf_lo(q.x), bf_lo(k.x), s); s = fmaf(bf_hi(q.x), bf_hi(k.x), s);
        s = fmaf(bf_lo(q.y), bf_lo(k.y), s); s = fmaf(bf_hi(q.y), bf_hi(k.y), s);
        s = fmaf(bf_lo(q.z), bf_lo(k.z), s); s = fmaf(bf_hi(q.z), bf_hi(k.z), s);
        s = fmaf(bf_lo(q.w), bf_lo(k.w), s); s = fmaf(bf_hi(q.w), bf_hi(k.w), s);
      }
      const float mn = fmaxf(m, s);
      const float ms = (mn == -INFINITY) ? 0.f : mn;
      const float corr = ex2(m - ms), p = ex2(s - ms);
      l = l * corr + p;
      m = mn;
      const float pb = __bfloat162float(__float2bfloat16(p));
#pragma unroll
      for (int c = 0; c < 4; c++) fma8(o + 8 * c, pb, __ldg(vr + c), corr);
    }
    const float sc = __fdividef(1.f, l);
    __nv_bfloat16* dst = op + (pass >> 1) * PANEL + (pass & 1) * 3584 + (tq >> 3) * 64 + (tq & 7);
#pragma unroll
    for (int d = 0; d < 32; d++) dst[(d >> 3) * 896 + (d & 7) * 8] = __float2bfloat16(o[d] * sc);
  }
}

__device__ __forceinline__ uint32_t launch_epoch() { return atomicAdd(&g_ticket, 1u) / gridDim.x; }

__global__ void __cluster_dims__(2, 1, 1) __launch_bounds__(384, 1) mha_fused_kernel(const __grid_constant__ Params prm) {
  extern __shared__ __align__(1024) unsigned char smem_raw[];

  const uint32_t sb = (smem_u32(smem_raw) + 1023u) & ~1023u;
  const uint32_t full0 = sb + SM_BAR, empty0 = full0 + 8 * NBAR, sfull0 = empty0 + 8 * NBAR;
  const uint32_t cred0 = sfull0 + 32, redo0 = cred0 + 64, epoch_addr = redo0 + 8, go_bar = redo0 + 16, ok_bar = redo0 + 24;
  const uint32_t rank = blockIdx.x & 1, pair = blockIdx.x >> 1;
  const uint32_t head = prm.head[pair];
  const int u_begin = head & 1023, u_end = u_begin + ((head >> 10) & 31);
  const uint32_t delay = ((head >> 15) & 255) * 256;
  const int tid = threadIdx.x;
  const int wid = __shfl_sync(0xffffffffu, tid >> 5, 0), wg = wid >> 2;

  if (wg == 2) {
    asm volatile("setmaxnreg.dec.sync.aligned.u32 %0;" ::"n"(504 - 2 * CREGS));
    const int warp = wid & 3, lane = tid & 31;
    bar_sync(0, 384);
    asm volatile("barrier.cluster.arrive.relaxed.aligned;" ::: "memory");
    if (warp < 3 && delay)
      asm volatile(
          "{\n.reg .pred p, q;\n.reg .u32 t0, t;\nmov.u32 t0, %%clock;\n"
          "SPIN:\nnanosleep.u32 100;\nmov.u32 t, %%clock;\nsub.u32 t, t, t0;\nsetp.lt.u32 p, t, %0;\n"
          "vote.sync.all.pred q, p, 0xffffffff;\n@q bra.uni SPIN;\n}" ::"r"(delay));
    auto slot_addr = [&](uint32_t i) { return sb + SM_RING + ring_slot(i) * SLOT; };
    auto full_bar = [&](uint32_t i) { return full0 + 8 * ring_slot(i); };
    const int count = (head >> 10) & 31;
    if (warp == 0) {
      uint32_t it = 6, prev = 0, code = head >> 23;
      auto acquire = [&](uint32_t i) { mbar_wait_warp(empty0 + 8 * ring_slot(i), ring_par(i) ^ 1); };
      uint32_t rblk = 0, rleft = 0;
      auto block_read = [&]() {
        asm volatile(ELECTED "red.relaxed.gpu.global.add.u32 [%0], 1;\n}" ::"l"(&g_rd[prm.blk[rblk] & 511]) : "memory");
        rblk++;
        rleft--;
      };
#pragma unroll 1
      for (int n = 1; n <= count; n++) {
        const uint32_t pat = unit_pattern(code, prev);
        const Unit u = decode_unit(code, rank);
        const int br = u.g >> 4;
        const CUtensorMap* mw = (u.attn ? prm.wq : prm.wo) + br;
        const int nslab = u.nslab;
#pragma unroll 1
        for (int k = n == 1 ? 2 : 0, pos = n == 1; k < nslab; k++) {
          const uint32_t i = it + (pos == 0);
          acquire(i);
          e_expect_tx(full_bar(i), SLOT);
          tma_ld3(slot_addr(i), mw, u.h0 * 256 + k * 64, u.hc * 2, full_bar(i), kEvictNormal);
          if (rleft && (k == 2 || k == 10 || (k >= 12 && (k & 3) == 0))) {
#pragma unroll 1
            do block_read();
            while (rleft && k == 2);
          }
          if (!u.attn && k == 4) rblk = u.g * 16 + u.h0, rleft = nslab >> 2;
          it = i + 1 + (pos == 0);
          pos = next_pos(pos, k, pat);
        }
        if (u.attn) {
          const int row0 = ((u.g & 15) * kH + u.hc) * kSk;
#pragma unroll 1
          for (int j = 0; j < kSk / 32; j++, it++) {
            acquire(it);
            e_expect_tx(full_bar(it), SLOT);
            const int isv = j == 31 || (j > 0 && !(j & 1));
            tma_ld4(slot_addr(it), &prm.kv[2 * isv + br], row0 / 8 + (((j + 1) >> 1) - isv) * 8, full_bar(it), kEvictFirst);
            if (j == kSk / 32 - 2) e_arrive(go_bar, 1);
          }
        }
        prev = code;
        code = prm.unit[u_begin + n];
      }
      if (rleft) {
        acquire(it + NSLOT - 1);
#pragma unroll 1
        while (rleft) block_read();
      }
    } else if (warp < 3) {
      asm volatile("barrier.cluster.wait.acquire.aligned;" ::: "memory");
      const int w = warp == 1 ? rank : rank ^ 1;
      uint32_t it = 6, nc = 0, pph = 0, go_ph = 0, prev = 0, code = head >> 23;
      uint32_t peer_cred0;
      asm("mapa.shared::cluster.u32 %0, %1, %2;" : "=r"(peer_cred0) : "r"(cred0), "r"(rank ^ 1));
#pragma unroll 1
      for (int n = 1; n <= count; n++) {
        const uint32_t pat = unit_pattern(code, prev);
        Unit u = decode_unit(code, rank);
        const CUtensorMap* mx = u.attn ? &prm.x[u.g >> 4] : &prm.o_ld;
        const int nslab = u.nslab;
        const bool polls = !u.attn && (warp == 1 || !u.mc);
        uint32_t done = 0, ready = 0;
        if (polls) {
          asm volatile("ld.volatile.shared.u32 %0, [%1];" : "=r"(done) : "r"(epoch_addr) : "memory");
          done *= 2;
        }
        const unsigned int* flags = g_cnt + u.g * 16 + (lane & 15);
        const uint64_t xpol = u.attn ? kEvictNormal : kEvictFirst;
        int xcol = n == 1 ? 128 : 0, xrow = (u.g & 15) * kSq + w * NQ;
#pragma unroll 1
        for (int k = n == 1 ? 2 : 0, pos = n == 1; k < nslab; k++) {
          if (polls && (k & 2) == 0) {
            const uint32_t hp = u.h0 + (k >> 2);
            if ((k & 1) == 0) {
              if (!(ready >> hp & 1)) ready = flags_wait(flags, done, 1u << hp);
              xrow = (prm.blk[u.g * 16 + hp] & 511) * (4 * kSq) + w * NQ;
            } else if (!(ready >> hp & 2)) {
              ready = flags_wait(flags, done, 0);
            }
          }
          const uint32_t i = it + 2 * w, q = pos - 1;
          const uint32_t fbar = full0 + 8 * (pos == 0 ? ring_slot(i) : NSLOT + 4 * w + q);
          const uint32_t dst = pos == 0 ? slot_addr(i) : sb + SM_PANEL + (4 * w + q) * PANEL;
          const uint32_t par = (pos == 0 ? ring_round(i) : pph >> q) & 1;
          pph ^= pos == 0 ? 0u : 1u << q;
          it += 1 + 2 * (pos == 0);
          pos = next_pos(pos, k, pat);
          mbar_wait_warp(fbar + 8 * NBAR, par ^ 1);
          e_expect_tx(fbar, PANEL);
          if (!u.mc) {
            tma_ld2(dst, mx, xcol, xrow, fbar, xpol);
          } else {
            if (warp == 1) {
              if (it > 10) mbar_wait_warp(cred0 + 8 * (nc & 7), (nc >> 3) & 1);
              tma_ld2_mc(dst, mx, xcol, xrow, fbar, xpol);
            } else if (it > 10) {
              asm volatile(ELECTED "mbarrier.arrive.shared::cluster.b64 _, [%0];\n}" ::"r"(peer_cred0 + 8 * (nc & 7)) : "memory");
            }
            nc += it > 10;
          }
          xcol += u.attn ? 64 : 0;
          xrow += u.attn ? 0 : kSq;
        }
        if (u.attn) {
          mbar_wait_warp(go_bar, go_ph);
          go_ph ^= 1;
          it += kSk / 32;
        }
        prev = code;
        code = prm.unit[u_begin + n];
      }
    } else {
      uint32_t epoch = 0, prev = 0;
      if (lane == 0) epoch = launch_epoch();
      epoch = __shfl_sync(0xffffffffu, epoch, 0);
      asm volatile("st.volatile.shared.u32 [%0], %1;" ::"r"(epoch_addr), "r"(epoch + 1) : "memory");
      auto publish = [&](unsigned int* p) {
        __syncwarp();
        asm volatile(ELECTED "red.release.gpu.global.add.u32 [%0], 1;\n}" ::"l"(p) : "memory");
      };
#pragma unroll 1
      for (int n = 0; n < count; n++) {
        const uint32_t code = prm.unit[u_begin + n], ph = n & 1;
        if (!(code & 0x8000u)) {
          const uint32_t blk = prm.blk[code & 511], gen = (blk >> 9) & 7;
          if (gen > 0) flag_wait(&g_rd[blk & 511], 5 * (epoch * (blk >> 12) + gen));
        }
        __syncwarp();
        e_arrive(ok_bar, 1);
        const bool clear = (code & 0xA000u) == 0x2000u;
        const uint32_t oc = clear ? prm.unit[u_begin + n + 1] : code;
        const Unit u = decode_unit(oc, rank);
        const int row = (u.g & 15) * kSq, cb = (u.g >> 4) * 10 + u.hc * 2;
        unsigned int* pc = g_pc + (oc >> 8 & 127) * 32 + rank;
        if (!(code & 0x8000u)) {
          if (clear) {
            uint4* o = reinterpret_cast<uint4*>(prm.op + (row + (lane >> 4)) * (2 * kD) + cb * 64) + (lane & 15);
#pragma unroll 1
            for (int r = 0; r < kSq / 2; r++, o += 4 * kD / 8) {
              *o = make_uint4(0, 0, 0, 0);
              __nanosleep(40);
            }
            publish(pc + 2 * (oc & 15));
          }
#pragma unroll 1
          for (int q = 0; q < 4; q++) mbar_wait_warp(sfull0 + 8 * q, ph);
          publish(&g_cnt[code & 511]);
        } else {
          const bool cleared = (prev & 0xA000u) == 0x2000u;
          if (u.h0) flag_wait(pc + 2 * (u.h0 - 1), epoch + 1);
          asm volatile("fence.proxy.async.global;" ::: "memory");
#pragma unroll 1
          for (int q = 0; q < 4; q++) {
            const int w = n + 1 < count ? q & 1 : q >> 1, t = n + 1 < count ? q >> 1 : q & 1;
            mbar_wait_warp(sfull0 + 8 * (2 * t + w), ph);
            fence_async_smem();
#pragma unroll 1
            for (int r = 0; r < NQ; r += ST_ROWS) {
              tma_st3(&prm.out, row + w * NQ + r, cb + t, sb + SM_PANEL + (4 * w + 2 + t) * PANEL + r * 128, u.h0 || cleared);
              asm volatile("cp.async.bulk.commit_group;" ::: "memory");
              if (n + 1 < count) asm volatile("cp.async.bulk.wait_group.read 0;" ::: "memory");
            }
            __syncwarp();
            e_arrive(empty0 + 8 * (NSLOT + 4 * w + 2 + t), 2);
          }
          if ((code & 15) != 15 && !cleared) {
            asm volatile("cp.async.bulk.wait_group 0;" ::: "memory");
            asm volatile("fence.proxy.async.global;" ::: "memory");
            publish(pc + 2 * (code & 15));
          }
        }
        prev = code;
      }
      asm volatile("cp.async.bulk.wait_group 0;" ::: "memory");
    }
  } else {
    const int tq = tid & 127, lane = tid & 31, warp = tq >> 5;
    if (tid == 0) {
#pragma unroll
      for (int i = 0; i < NBAR; i++) {
        mbar_init(full0 + 8 * i, 1);
        mbar_init(empty0 + 8 * i, 2);
      }
#pragma unroll
      for (int i = 0; i < 12; i++) mbar_init(sfull0 + 8 * i, i < 4 ? 4 : 1);
      mbar_init(go_bar, 1);
      mbar_init(ok_bar, 1);
      asm volatile("st.shared.v4.u32 [%0], {%1, %1, %1, %1};" ::"r"(redo0), "r"(0) : "memory");
      asm volatile("fence.mbarrier_init.release.cluster;" ::: "memory");
      fence_async_smem();
    }
    if (wid == 0) {
      __syncwarp();
      const Unit u = decode_unit(head >> 23, rank);
#pragma unroll
      for (int i = 0; i < 6; i++) {
        e_expect_tx(full0 + 8 * i, i % 3 == 1 ? SLOT : PANEL);
        if (i % 3 == 1) tma_ld3(sb + SM_RING + i * SLOT, &prm.wq[u.g >> 4], i / 3 * 64, u.hc * 2, full0 + 8 * i, kEvictNormal);
        else tma_ld2(sb + SM_RING + i * SLOT, &prm.x[u.g >> 4], i / 3 * 64, (u.g & 15) * kSq + i % 3 / 2 * NQ, full0 + 8 * i, kEvictNormal);
      }
    } else if (wid < 5) {
      asm volatile(ELECTED "prefetch.tensormap [%0];\n}" ::"l"(prm.x + 2 * (wid - 1) + (head >> 31)) : "memory");
    }
    bar_sync(0, 384);
    asm volatile("barrier.cluster.arrive.relaxed.aligned;" ::: "memory");
    asm volatile("setmaxnreg.inc.sync.aligned.u32 %0;" ::"n"(CREGS));
    const uint32_t stage = sb + SM_PANEL + wg * 4 * PANEL;
    const uint32_t st_q = __shfl_sync(
        0xffffffffu, stage + ((lane >> 4) * 8 + (lane & 7)) * 128 + (((2 * warp + ((lane >> 3) & 1)) ^ (lane & 7)) << 4), lane);
    const uint32_t st_p = st_q + 2 * PANEL;
    const uint32_t dq = mk_desc(stage), dring = mk_desc(sb + SM_RING);
    float acc[2][56], s[56] = {};
    const int never = (sb >> 24) & ~1u;
    uint32_t it = 0, pph = 0;
    auto wait_full = [&](uint32_t i) { mbar_wait_warp(full0 + 8 * ring_slot(i), ring_par(i)); };
    auto test = [&](uint32_t bar, uint32_t par) { return mbar_test_if(bar, par, warp == 0); };
    auto probe = [&](uint32_t i) { return test(full0 + 8 * ring_slot(i), ring_par(i)); };
    auto release = [&](uint32_t i) { mbar_arrive1_if(empty0 + 8 * ring_slot(i), tq == 0); };
    auto slot_desc = [&](uint32_t i) { return dring + ring_slot(i) * (SLOT >> 4); };
    if (wg == 1) bar_arrive(1, 256);

    struct Fin {
      uint32_t rp[16];
      char* dst;
    };
    uint32_t ps[14] = {};
    float l[28] = {};
    auto step_sums = [&]() {
#pragma unroll
      for (int g = 0; g < 14; g++) asm("add.rn.bf16x2 %0, %0, %1;" : "+r"(ps[g]) : "r"(pack_bf16(l[2 * g], l[2 * g + 1])));
#pragma unroll
      for (int q = 0; q < 3; q++) stsm_x4_t(st_p + q * 2048, ps[2 * q], ps[2 * q + 7], ps[2 * q + 1], ps[2 * q + 8]);
      asm volatile("stmatrix.sync.aligned.m8n8.x2.trans.shared.b16 [%0], {%1, %2};" ::"r"(st_p + 3 * 2048), "r"(ps[6]), "r"(ps[13])
                   : "memory");
    };
    auto flag_bad = [&](bool bad) {
      asm volatile("{\n.reg .pred p;\nsetp.ne.u32 p, %1, 0;\n@p st.shared.u32 [%0], %1;\n}" ::"r"(redo0 + 4 * wg), "r"((uint32_t)bad)
                   : "memory");
    };
    auto step_finite = [&](bool live) {
      uint32_t z[4] = {0, 0, 0, 0};
#pragma unroll
      for (int i = 0; i < 28; i++)
        asm volatile("fma.rn.bf16x2 %0, %1, %2, %0;" : "+r"(z[i & 3]) : "r"(__float_as_uint(s[2 * i])), "r"(__float_as_uint(s[2 * i + 1])));
      asm volatile("add.rn.bf16x2 %0, %0, %1;" : "+r"(z[0]) : "r"(z[1]));
      asm volatile("add.rn.bf16x2 %0, %0, %1;" : "+r"(z[2]) : "r"(z[3]));
      asm volatile("add.rn.bf16x2 %0, %0, %1;" : "+r"(z[0]) : "r"(z[2]));
      flag_bad(live && (((z[0] & 0x7F807F80u) + 0x00800080u) & 0x80008000u));
    };
    auto rows_addr = [&]() {
      const uint32_t q = min(tq, NQ - 1), hi = q >= 56, n = q - 56 * hi;
      return stage + 2 * PANEL + n * 128 + ((hi ^ (n & 7)) << 4);
    };
    auto rows_load = [&](Fin& f, uint32_t a) {
#pragma unroll
      for (int c = 0; c < 4; c++)
        asm volatile("ld.shared.v4.u32 {%0, %1, %2, %3}, [%4];"
                     : "=r"(f.rp[4 * c]), "=r"(f.rp[4 * c + 1]), "=r"(f.rp[4 * c + 2]), "=r"(f.rp[4 * c + 3])
                     : "r"(a ^ (c << 5))
                     : "memory");
    };
    auto step_rows = [&](const Fin& f, bool live) {
      const uint32_t q = min(tq, NQ - 1);
      float t = 0.f, t2 = 0.f;
#pragma unroll
      for (int i = 0; i < 8; i++) {
        uint32_t v;
        asm("add.rn.bf16x2 %0, %1, %2;" : "=r"(v) : "r"(f.rp[2 * i]), "r"(f.rp[2 * i + 1]));
        t += bf_lo(v), t2 += bf_hi(v);
      }
      t += t2;
      float r;
      asm("rcp.approx.ftz.f32 %0, %1;" : "=f"(r) : "f"(t));
      asm volatile("st.shared.u16 [%0], %1;" ::"r"(sb + SM_RCP + wg * 320 + (q >> 1 & 3) * 80 + (q >> 3) * 4 + (q & 1) * 2),
                   "h"((uint16_t)pack_bf16(r, r))
                   : "memory");
      flag_bad(live && !(t >= 9.094947017729282e-13f && t <= 1.329227995784916e36f));
    };
    auto step_scales = [&](Fin& f) {
#pragma unroll
      for (int c = 0; c < 4; c++)
        asm volatile("ld.shared.v4.u32 {%0, %1, %2, %3}, [%4];"
                     : "=r"(f.rp[4 * c]), "=r"(f.rp[4 * c + 1]), "=r"(f.rp[4 * c + 2]), "=r"(f.rp[4 * c + 3])
                     : "r"(sb + SM_RCP + wg * 320 + (lane & 3) * 80 + c * 16)
                     : "memory");
    };
    auto o_base = [&](uint32_t u) {
      return reinterpret_cast<char*>(g_o) + (size_t)((((prm.blk[u & 511] & 511u) * 4 + rank * 2) * 2 + wg) * (uint32_t)PANEL);
    };
    auto step_write = [&](const Fin& f, int lo, int hi) {
#pragma unroll
      for (int i = lo; i < hi; i++) {
        uint32_t v = __float_as_uint(s[i]);
        asm("mul.rn.bf16x2 %0, %0, %1;" : "+r"(v) : "r"(f.rp[(i % 28) >> 1]));
        s[i] = __uint_as_float(v);
        asm volatile("st.global.u32 [%0], %1;" ::"l"(f.dst + (i / 28) * 2 * PANEL + (i & 1) * 1792 + ((i % 28) >> 1) * 128), "r"(v) : "memory");
      }
    };
    auto keep_alive = [&](int lo, int hi, int c) {
      if (never == c) {
#pragma unroll
        for (int i = lo; i < hi; i++) asm volatile("st.shared.f32 [%0], %1;" ::"r"(stage + 4 * i), "f"(s[i]) : "memory");
        pin_order(never, c);
      }
    };
    auto step_signal = [&](int t) {
      __syncwarp();
      mbar_arrive1_if(sfull0 + 8 * (2 * t + wg), lane == 0);
    };
    auto free_panel = [&](int q) { mbar_arrive1_if(empty0 + 8 * (NSLOT + 4 * wg + q), tq < 2); };
    auto read_verdict = [&]() {
      uint32_t redo;
      asm volatile("ld.shared.u32 %0, [%1];" : "=r"(redo) : "r"(redo0 + 4 * wg) : "memory");
      return redo;
    };
    auto step_redo = [&](uint32_t prev) {
      asm volatile("" : "+r"(prev));
      bar_sync(3 + wg, 128);
      if (tq == 0) asm volatile("st.shared.u32 [%0], %1;" ::"r"(redo0 + 4 * wg), "r"(0) : "memory");
      const Unit u = decode_unit(prev & 511, rank);
      const int br = u.g >> 4, b = u.g & 15;
      const size_t off = (size_t)(b * kH + u.hc) * kSk * kDh;
      slow_rows(g_qrow + (blockIdx.x * 2 + wg) * (16 * 128) + tq, tq, prm.xp[br] + (b * kSq + wg * NQ) * kD, prm.wp[br] + u.hc * kDh,
                prm.kp[br] + off, prm.vp[br] + off, reinterpret_cast<__nv_bfloat16*>(o_base(prev)));
#pragma unroll
      for (int i = 0; i < 56; i++) s[i] = 0.f;
    };
    auto issue_slab = [&](uint32_t da, uint32_t db, int accum, auto split, auto tb) {
      constexpr int TB = tb.value, KS = TB ? 224 : 2;
      if (TB) db += 111 << 16;
      if (split.value == 1) {
#pragma unroll
        for (int t = 0; t < 2; t++) {
#pragma unroll
          for (int kk = 0; kk < 4; kk++) {
            if (t == 1 && kk == 2) bar_arrive(2 - wg, 256);
            if (TB) wgmma_n112<1, 1>(acc[t], da + t * 512 + kk * 128, db + kk * KS, 1);
            else wgmma_n112<1, 0, 1>(acc[t], da + t * 64 + kk * 256, db + kk * KS, 1);
          }
          wgmma_commit();
        }
      } else {
#pragma unroll
        for (int kk = 0; kk < 4; kk++) {
          if (kk == 3) bar_arrive(2 - wg, 256);
          wgmma_n112<1, TB>(acc[0], da + kk * 128, db + kk * KS, kk > 0 ? 1 : accum);
          wgmma_n112<1, TB>(acc[1], da + 512 + kk * 128, db + kk * KS, kk > 0 ? 1 : accum);
        }
        wgmma_commit();
      }
    };

    uint32_t code = head >> 23, prev = 0, pend = 0, uph = 0;
    uint32_t da = slot_desc(1), db = slot_desc(2 * wg);
    auto next_unit = [&](bool block) {
      da = slot_desc(it + 1), db = slot_desc(it + 2 * wg);
      if (block) {
        if (!__all_sync(0xffffffffu, probe(it + 1) & probe(it + 2 * wg))) {
          wait_full(it + 1);
          wait_full(it + 2 * wg);
        }
      }
    };
    wait_full(1);
    wait_full(2 * wg);
    for (int left = (head >> 10) & 31; left > 0; left--) {
      const int ui = u_end - left;
      uint32_t nxt;
      bool defer;
      auto peek = [&]() {
        const uint32_t cur = prm.unit[ui];
        nxt = __shfl_sync(0xffffffffu, (uint32_t)prm.unit[ui + 1], 0);
        defer = left > 1 && (!(nxt & 0x8000u) || (cur & 0xC000u) == 0x4000u);
      };
      const bool out = code & 0x8000u;
      uint32_t rel = 0;
      auto retire = [&]() {
        wgmma_wait<0>();
        fence_regs(acc[0]);
        fence_regs(acc[1]);
        mbar_arrive1_if(rel, rel);
        rel = 0;
      };
      auto turn = [&](int accum, auto mode, auto tb, auto first) {
        bar_sync(1 + wg, 256);
        if (!first.value) retire();
        wgmma_fence();
        issue_slab(da, db, accum, mode, tb);
      };
      auto take_turn = [&](int accum, auto mode, auto first) {
        if (out) turn(accum, mode, IntC<1>{}, first);
        else turn(accum, mode, IntC<0>{}, first);
      };
      Fin f;
      int k = 0;
      const bool staged = pend == 2;
      if (out ? pend == 1 : !staged) {
        uint32_t redo = 0;
        static_for<0, 8>([&](auto kc) {
          constexpr int k = kc.value;
          take_turn(k > 0, IntC<0>{}, BoolC<k == 0>{});
          if (k >= 4) keep_alive(w_cut(k - 4), w_cut(k - 3), 62 + 2 * k);
          if (k == 0 && pend) step_sums();
          if (k == 2) step_scales(f);
          constexpr int p0 = x_pos(0, k), p1 = x_pos(0, k + 1), o0 = x_off(0, k), o1 = x_off(0, k + 1);
          const uint32_t rw = empty0 + 8 * ring_slot(it + o0 + (p0 == 0));
          const uint32_t rx = empty0 + 8 * (p0 == 0 ? ring_slot(it + o0 + 2 * wg) : NSLOT + 4 * wg + p0 - 1);
          const uint32_t wi = it + o1 + (p1 == 0), xi = it + o1 + 2 * wg;
          const uint32_t xbar = full0 + 8 * (p1 == 0 ? ring_slot(xi) : NSLOT + 4 * wg + p1 - 1);
          const uint32_t xpar = (p1 == 0 ? ring_round(xi) : pph >> (p1 == 0 ? 0 : p1 - 1)) & 1;
          if constexpr (p1 != 0) pph ^= 1u << (p1 - 1);
          uint32_t okp = probe(wi) & test(xbar, xpar);
          if (k == 2) okp &= test(ok_bar, uph ^ pend);
          rel = pick(tq == 0, rw, pick(tq < 3 && (k < 6 || out), rx, 0));
          if (k == 0) {
            const uint32_t a = rows_addr();
            bar_sync(3 + wg, 128);
            rows_load(f, a);
          }
          if (k == 1) {
            mbar_arrive1_if(empty0 + 8 * (NSLOT + 4 * wg + 2), tq < 2 && pend);
            step_rows(f, pend);
          }
          if (k == 2) {
            step_finite(pend);
            f.dst = o_base(prev) + warp * 3584 + lane * 4;
          }
          if (k == 6) redo = read_verdict();
          if (k >= 3 && pend) step_write(f, w_cut(k - 3), w_cut(k - 2));
          if (k == 7) {
            if (__any_sync(0xffffffffu, redo)) step_redo(prev);
            __syncwarp();
            mbar_arrive1_if(sfull0 + 8 * (2 * lane + wg), lane < 2 && pend);
          }
          const bool ok = __all_sync(0xffffffffu, okp);
          da = slot_desc(wi);
          db = p1 == 0 ? slot_desc(xi) : dq + (p1 - 1) * (PANEL >> 4);
          if (!ok) {
            retire();
            wait_full(wi);
            mbar_wait_warp(xbar, xpar);
            if (k == 2) mbar_wait_warp(ok_bar, uph ^ pend);
          }
        });
        k = 8;
      }
      const int nslab = unit_slabs(code);
      uint32_t pos = k ? 3 : 0, wi = it + (k ? 12 : 1), xbar = full0 + 8 * (k ? NSLOT + 4 * wg + 2 : ring_slot(it + 2 * wg));
      const int kend = out ? nslab - 1 : 8;
      if (k < kend) {
        uint32_t r = it + (k ? 13 : 3);
        const uint32_t pat = staged ? kPat1 : kPat0;
        const uint32_t keep_pos = out ? 3 : 1;
        const int keep_k = nslab == 8 ? 4 : nslab - 5;
#pragma unroll 1
        do {
          take_turn(k > 0, IntC<0>{}, BoolC<false>{});
          rel = pick(tq == 0, empty0 + 8 * ring_slot(wi), pick(tq < 3 && (pos < keep_pos || k < keep_k), xbar + 8 * NBAR, 0));
          pos = next_pos(pos, k, pat);
          const bool ring = pos == 0;
          const uint32_t i = r + 2 * wg, q = pos - 1;
          wi = ring ? r + 1 : r;
          xbar = full0 + 8 * (ring ? ring_slot(i) : NSLOT + 4 * wg + q);
          const uint32_t xpar = (ring ? ring_round(i) : pph >> q) & 1;
          da = slot_desc(wi);
          db = ring ? slot_desc(i) : dq + q * (PANEL >> 4);
          pph ^= ring ? 0u : 1u << q;
          r += ring ? 3 : 1;
          const bool job = staged && k < 2;
          if (job || !__all_sync(0xffffffffu, probe(wi) & test(xbar, xpar))) {
            if (!job) {
              retire();
            } else {
              if (k == 0) store_half<0>(st_p, s);
              else store_half<1>(st_p, s);
              step_signal(k);
            }
            wait_full(wi);
            mbar_wait_warp(xbar, xpar);
          }
        } while (++k < kend);
      }
      if (!out) {
        it += staged ? x_off(1, 10) : x_off(0, 10);
        {
          const uint32_t x9 = full0 + 8 * (NSLOT + 4 * wg + 3), p9 = pph >> 3 & 1, d9 = slot_desc(it - 1);
          pph ^= 8;
          if (!__all_sync(0xffffffffu, probe(it - 1) & test(x9, p9))) {
            retire();
            wait_full(it - 1);
            mbar_wait_warp(x9, p9);
          }
          bar_sync(1 + wg, 256);
          retire();
          wgmma_fence();
#pragma unroll
          for (int t = 0; t < 2; t++) {
#pragma unroll
            for (int kk = 0; kk < 8; kk++)
              wgmma_n112<1>(acc[t], (kk < 4 ? da : d9) + t * 512 + (kk & 3) * 128, db + t * never + (kk >> 2) * (PANEL >> 4) + (kk & 3) * 2, 1);
            wgmma_commit();
          }
          bar_arrive(2 - wg, 256);
          keep_alive(w_cut(4), w_cut(5), 80);
          const bool ok = __all_sync(0xffffffffu, probe(it));
          rel = pick(tq < 2, empty0 + 8 * pick(tq == 0, ring_slot(it - 2), ring_slot(it - 1)), 0);
          da = slot_desc(it);
          wgmma_wait<1>();
          fence_regs(acc[0]);
          q_half<0>(st_q, s, acc[0], never);
          wgmma_wait<0>();
          fence_regs(acc[1]);
          q_half<1>(st_q, s, acc[1], never);
          mbar_arrive1_if(rel, rel);
          if (!ok) wait_full(it);
        }
        fence_async_smem();
        auto issue_s = [&](uint32_t dk, int accum) {
          wgmma_fence();
#pragma unroll
          for (int kk = 0; kk < 8; kk++)
            wgmma_n112<0, 0, 1>(s, dk + (kk >> 2) * 64 + (kk & 3) * 2, dq + (kk >> 2) * (PANEL >> 4) + (kk & 3) * 2, kk > 0 ? 1 : accum);
          wgmma_commit();
        };
        auto add_sums = [&]() {
#pragma unroll
          for (int jj = 0; jj < 14; jj++)
            asm volatile("{\n.reg .b32 t;\nshl.b32 t, %2, 16;\nadd.f32 %0, %0, t;\nand.b32 t, %2, 0xffff0000;\nadd.f32 %1, %1, t;\n}"
                         : "+f"(l[2 * jj]), "+f"(l[2 * jj + 1])
                         : "r"(ps[jj]));
        };
        auto softmax = [&](uint32_t par, int pin0) {
          const uint32_t pa = st_p + par * PANEL;
#pragma unroll
          for (int i = 0; i < 8 + SM_OFF; i++) s[i] = ex2(s[i]);
#pragma unroll
          for (int jj = 0; jj < 7; jj++) {
            const float* e = s + 8 * jj;
#pragma unroll
            for (int i = 8 * jj + 8 + SM_OFF; i < 8 * jj + 16 + SM_OFF; i++)
              if (i < 56) s[i] = ex2(s[i]);
            const uint32_t p0 = pack_bf16(e[0], e[1]), p1 = pack_bf16(e[2], e[3]), p2 = pack_bf16(e[4], e[5]), p3 = pack_bf16(e[6], e[7]);
            stsm_x4_t_pin(pa + jj * 2048, p0, p1, p2, p3, never, pin0);
            asm("add.rn.bf16x2 %0, %1, %2;" : "=r"(ps[2 * jj]) : "r"(p0), "r"(p1));
            asm("add.rn.bf16x2 %0, %1, %2;" : "=r"(ps[2 * jj + 1]) : "r"(p2), "r"(p3));
          }
        };
        bar_sync(1 + wg, 256);
        issue_s(da, never);
        bar_arrive(2 - wg, 256);
        {
#pragma unroll
          for (int i = 0; i < 28; i++) asm volatile("mov.b32 %0, 0;" : "=f"(l[i]));
          peek();
          const bool ok = __all_sync(0xffffffffu, probe(it + 1));
          da = slot_desc(it + 1);
          wgmma_wait_pin<0>(never, 180);
          fence_regs(s);
          release(it);
          softmax(0, 176);
          if (!ok) wait_full(it + 1);
        }
        it += 1;
#pragma unroll 1
        for (int j = 1; j < 16; j++) {
          fence_async_smem();
          bar_sync(1 + wg, 256);
          issue_s(da, 0);
          pin_order(never, 2 * j + 128);
          const uint32_t okv = mbar_test(full0 + 8 * ring_slot(it + 1), ring_par(it + 1));
          const uint32_t okk = probe(it + 2);
          da = slot_desc(it + 2);
          add_sums();
          const bool ok = __all_sync(0xffffffffu, okk);
          if (!__all_sync(0xffffffffu, okv)) wait_full(it + 1);
          {
            const uint32_t dv = slot_desc(it + 1), dp = dq + (3 - (j & 1)) * (PANEL >> 4);
            wgmma_fence();
#pragma unroll
            for (int kk = 0; kk < 4; kk++) {
              wgmma_n112<1, 0, 1>(acc[0], dv + kk * 256, dp + kk * 2, kk > 0 ? 1 : j > 1);
              wgmma_n112<1, 0, 1>(acc[1], dv + 64 + kk * 256, dp + kk * 2, kk > 0 ? 1 : j > 1);
            }
          }
          wgmma_commit();
          bar_arrive(2 - wg, 256);
          wgmma_wait<1>();
          fence_regs(s);
          release(it);
          softmax(j & 1, 2 * j + 192);
          wgmma_wait<0>();
          fence_regs(acc[0]);
          fence_regs(acc[1]);
          release(it + 1);
          it += 2;
          if (!ok) {
            wait_full(it);
          }
        }
        it += 1;
        fence_async_smem();
        bar_sync(1 + wg, 256);
        wgmma_fence();
        issue_slab(da, dq + 3 * (PANEL >> 4), 1, IntC<1>{}, IntC<0>{});
        pin_order(never, 182);
        mbar_arrive1_if(empty0 + 8 * (NSLOT + 4 * wg + (tq >> 1)), tq < 4);
        rel = pick(tq == 0, empty0 + 8 * ring_slot(it - 1), pick(tq < 3, empty0 + 8 * (NSLOT + 4 * wg + 3), 0));
        next_unit(defer);
        wgmma_wait<1>();
        fence_regs(acc[0]);
        pack_half<0>(s, acc[0]);
        fence_half<0>(s);
        wgmma_wait_pin<0>(never, 172);
        fence_regs(acc[1]);
        mbar_arrive1_if(rel, rel);
        pack_half<1>(s, acc[1]);
        pend = 1;
      } else {
        turn(1, IntC<1>{}, IntC<1>{}, BoolC<false>{});
        pin_order(never, 186);
        it += nslab + 2 * (2 + (nslab - 6) / 5);
        peek();
#pragma unroll
        for (int i = 0; i < 28; i++) ps[i >> 1] = 0, l[i] = 0.f;
        next_unit(defer);
        mbar_wait_warp(ok_bar, uph);
        rel = pick(tq == 0, empty0 + 8 * ring_slot(wi), pick(tq < 3 && pos < 3, xbar + 8 * NBAR, 0));
        wgmma_wait<1>();
        fence_regs(acc[0]);
        pack_half<0>(s, acc[0]);
        fence_half<0>(s);
        wgmma_wait_pin<0>(never, 174);
        fence_regs(acc[1]);
        mbar_arrive1_if(rel, rel);
        pack_half<1>(s, acc[1]);
        pend = 2;
      }
      if (!defer) {
        if (pend == 1) step_sums();
        bar_sync(3 + wg, 128);
        if (pend == 2) {
          store_half<0>(st_p, s);
          step_signal(0);
          store_half<1>(st_p, s);
        } else {
          rows_load(f, rows_addr());
          step_finite(true);
          step_rows(f, true);
          mbar_wait_warp(ok_bar, uph);
          bar_sync(3 + wg, 128);
          free_panel(2);
          step_scales(f);
          if (__any_sync(0xffffffffu, read_verdict())) {
            step_redo(code);
          } else {
            f.dst = o_base(code) + warp * 3584 + lane * 4;
            step_write(f, 0, 56);
          }
          step_signal(0);
        }
        step_signal(1);
        pend = 0;
#pragma unroll
        for (int i = 0; i < 28; i++) ps[i >> 1] = 0, l[i] = 0.f;
        if (left > 1) {
          wait_full(it + 1);
          wait_full(it + 2 * wg);
        }
      }
      prev = code, code = nxt, uph ^= 1;
    }
    if (wg == 0) bar_sync(1, 256);
  }
}

typedef CUresult (*EncodeFn)(CUtensorMap*, CUtensorMapDataType, cuuint32_t, void*, const cuuint64_t*, const cuuint64_t*,
                             const cuuint32_t*, const cuuint32_t*, CUtensorMapInterleave, CUtensorMapSwizzle,
                             CUtensorMapL2promotion, CUtensorMapFloatOOBfill);

bool encode(EncodeFn fn, CUtensorMap* m, const void* ptr, int rank, const cuuint64_t* dims, const cuuint64_t* strides,
            const cuuint32_t* box, CUtensorMapL2promotion promo, CUtensorMapSwizzle swz = CU_TENSOR_MAP_SWIZZLE_128B) {
  const cuuint32_t es[4] = {1, 1, 1, 1};
  return fn(m, CU_TENSOR_MAP_DATA_TYPE_BFLOAT16, rank, const_cast<void*>(ptr), dims, strides, box, es,
            CU_TENSOR_MAP_INTERLEAVE_NONE, swz, promo,
            CU_TENSOR_MAP_FLOAT_OOB_FILL_NONE) == CUDA_SUCCESS;
}
bool encode_panels(EncodeFn fn, CUtensorMap* m, const void* ptr, uint64_t rows, uint64_t cols, uint32_t box_rows,
                   uint32_t box_blocks = 2) {
  const cuuint64_t dims[3] = {64, rows, cols / 64};
  const cuuint64_t strides[2] = {cols * 2, 128};
  const cuuint32_t box[3] = {64, box_rows, box_blocks};
  CUtensorMapL2promotion promo = CU_TENSOR_MAP_L2_PROMOTION_L2_128B;
  return encode(fn, m, ptr, 3, dims, strides, box, promo);
}
bool encode_kv(EncodeFn fn, CUtensorMap* m, const void* ptr) {
  const cuuint64_t dims[4] = {64, 8, 2, (uint64_t)kB * kH * kSk / 8};
  const cuuint64_t strides[3] = {kDh * 2, 128, 8 * kDh * 2};
  const cuuint32_t box[4] = {64, 8, 2, 8};
  CUtensorMapL2promotion promo = CU_TENSOR_MAP_L2_PROMOTION_L2_128B;
  return encode(fn, m, ptr, 4, dims, strides, box, promo);
}
bool encode_2d(EncodeFn fn, CUtensorMap* m, const void* ptr, uint64_t rows, uint64_t cols, uint32_t box_rows,
               CUtensorMapSwizzle swz = CU_TENSOR_MAP_SWIZZLE_128B) {
  const cuuint64_t dims[2] = {cols, rows};
  const cuuint64_t strides[1] = {cols * 2};
  const cuuint32_t box[2] = {64, box_rows};
  CUtensorMapL2promotion promo = CU_TENSOR_MAP_L2_PROMOTION_L2_128B;
  return encode(fn, m, ptr, 2, dims, strides, box, promo, swz);
}

constexpr int kTunedPairs = 66;
const uint16_t kTunedBlock[kAttnUnits] = {
    20480, 20486, 20492, 20498, 20504, 20510, 20516, 20522, 20528, 20534, 16444, 16450, 16456, 16462, 20996, 21002,
    20481, 20487, 20493, 20499, 20505, 20511, 20517, 20523, 20529, 20535, 16445, 16451, 16457, 16463, 20997, 21003,
    20482, 20488, 20494, 20500, 20506, 20512, 20518, 20524, 20530, 20536, 16446, 16452, 16458, 20992, 20998, 21004,
    20483, 20489, 20495, 20501, 20507, 20513, 20519, 20525, 20531, 20537, 16447, 16453, 16459, 20993, 20999, 21005,
    20484, 20490, 20496, 20502, 20508, 20514, 20520, 20526, 20532, 20538, 16448, 16454, 16460, 20994, 21000, 21006,
    20485, 20491, 20497, 20503, 20509, 20515, 20521, 20527, 20533, 20539, 16449, 16455, 16461, 20995, 21001, 21007,
    21008, 21012, 21016, 21020, 21024, 21028, 21032, 21036, 21040, 21044, 21048, 16956, 16960, 16964, 16968, 16972,
    21009, 21013, 21017, 21021, 21025, 21029, 21033, 21037, 21041, 21045, 21049, 16957, 16961, 16965, 16969, 16973,
    21010, 21014, 21018, 21022, 21026, 21030, 21034, 21038, 21042, 21046, 21050, 16958, 16962, 16966, 16970, 16974,
    21011, 21015, 21019, 21023, 21027, 21031, 21035, 21039, 21043, 21047, 21051, 16959, 16963, 16967, 16971, 16975,
    21504, 21506, 21508, 21510, 21512, 21514, 21516, 21518, 21520, 21522, 21524, 21526, 21528, 21530, 21532, 21534,
    21505, 21507, 21509, 21511, 21513, 21515, 21517, 21519, 21521, 21523, 21525, 21527, 21529, 21531, 21533, 21535,
    21536, 21540, 21544, 21548, 21552, 21556, 21560, 17468, 17472, 17476, 17480, 17484, 22016, 22020, 22024, 22028,
    21537, 21541, 21545, 21549, 21553, 21557, 21561, 17469, 17473, 17477, 17481, 17485, 22017, 22021, 22025, 22029,
    21538, 21542, 21546, 21550, 21554, 21558, 21562, 17470, 17474, 17478, 17482, 17486, 22018, 22022, 22026, 22030,
    21539, 21543, 21547, 21551, 21555, 21559, 21563, 17471, 17475, 17479, 17483, 17487, 22019, 22023, 22027, 22031,
    22032, 22034, 22036, 22038, 22040, 22042, 22044, 22046, 22048, 22050, 22052, 22054, 22056, 22058, 22060, 22062,
    22033, 22035, 22037, 22039, 22041, 22043, 22045, 22047, 22049, 22051, 22053, 22055, 22057, 22059, 22061, 22063,
    22064, 22066, 22068, 22070, 22072, 22074, 17980, 17982, 17984, 17986, 17988, 17990, 17992, 17994, 17996, 17998,
    22065, 22067, 22069, 22071, 22073, 22075, 17981, 17983, 17985, 17987, 17989, 17991, 17993, 17995, 17997, 17999,
    22528, 22529, 22530, 22531, 22532, 22533, 22534, 22535, 22536, 22537, 22538, 22539, 22540, 22541, 22542, 22543,
    22544, 22545, 22546, 22547, 22548, 22549, 22550, 22551, 22552, 22553, 22554, 22555, 22556, 22557, 22558, 22559,
    22560, 22570, 22580, 4178, 4188, 4198, 4208, 4218, 4228, 4238, 4248, 4258, 4268, 4278, 4288, 4298,
    22561, 22571, 22581, 4179, 4189, 4199, 4209, 4219, 4229, 4239, 4249, 4259, 4269, 4279, 4289, 4299,
    22562, 22572, 22582, 4180, 4190, 4200, 4210, 4220, 4230, 4240, 4250, 4260, 4270, 4280, 4290, 4300,
    22563, 22573, 22583, 4181, 4191, 4201, 4211, 4221, 4231, 4241, 4251, 4261, 4271, 4281, 4291, 4301,
    22564, 22574, 22584, 4182, 4192, 4202, 4212, 4222, 4232, 4242, 4252, 4262, 4272, 4282, 4292, 4302,
    22565, 22575, 22585, 4183, 4193, 4203, 4213, 4223, 4233, 4243, 4253, 4263, 4273, 4283, 4293, 4303,
    22566, 22576, 22586, 4184, 4194, 4204, 4214, 4224, 4234, 4244, 4254, 4264, 4274, 4284, 4294, 4304,
    22567, 22577, 22587, 4185, 4195, 4205, 4215, 4225, 4235, 4245, 4255, 4265, 4275, 4285, 4295, 4305,
    22568, 22578, 4176, 4186, 4196, 4206, 4216, 4226, 4236, 4246, 4256, 4266, 4276, 4286, 4296, 4306,
    22569, 22579, 4177, 4187, 4197, 4207, 4217, 4227, 4237, 4247, 4257, 4267, 4277, 4287, 4297, 4307};
const uint8_t kTunedLen[kTunedPairs] = {
    10, 10, 10, 10, 10, 10, 10, 9, 9, 11, 9, 11, 10, 10, 10, 10, 8, 9, 11, 8, 9, 10, 10, 11, 9, 9, 10, 10, 11, 10, 10, 11, 9,
    9, 10, 9, 9, 11, 10, 10, 9, 10, 11, 10, 10, 10, 10, 10, 9, 11, 10, 10, 10, 9, 10, 10, 10, 9, 10, 11, 10, 9, 10, 10, 9, 10};
const uint8_t kTunedDelay[kTunedPairs] = {
    0, 0, 0, 0, 0, 29, 5, 0, 105, 1, 0, 0, 1, 0, 1, 0, 0, 0, 0, 109, 109, 29,
    0, 0, 15, 111, 0, 31, 3, 7, 1, 0, 0, 105, 7, 72, 0, 0, 0, 0, 0, 1, 7, 0,
    0, 23, 5, 1, 0, 3, 1, 3, 0, 0, 7, 13, 0, 0, 0, 17, 35, 0, 0, 0, 115, 0};
const uint16_t kTunedUnit[] = {
    0, 37388, 178, 231, 266, 328, 403, 441, 8655, 55809, 50, 47, 140, 242, 239, 313, 416, 422,
    16860, 58511, 37, 93, 123, 210, 223, 297, 400, 406, 25036, 58375, 81, 95, 16508, 39177, 220, 293,
    348, 437, 16891, 60031, 52, 30, 153, 240, 24782, 48396, 417, 439, 16877, 62127, 25, 36870, 149, 170,
    235, 16691, 49471, 375, 25005, 61445, 71, 34053, 100, 179, 200, 269, 336, 388, 25018, 64778, 64, 38156,
    177, 230, 263, 16710, 51469, 54538, 53767, 26, 132, 180, 248, 286, 335, 372, 25002, 57866, 70, 129,
    110, 211, 255, 45057, 317, 497, 376, 16814, 58047, 18, 32775, 16509, 40207, 16662, 49679, 469, 16780, 53903,
    5, 31, 154, 16625, 43522, 47113, 301, 465, 503, 16782, 54719, 38, 13, 121, 224, 253, 295, 352,
    358, 24988, 57351, 36, 79, 16539, 41999, 45316, 16680, 49279, 484, 16779, 61551, 6, 78, 137, 192, 43583,
    316, 449, 487, 24958, 63492, 35, 15, 16522, 41231, 47621, 299, 369, 359, 24989, 58630, 16, 33039, 167,
    233, 271, 16724, 52495, 57615, 66, 33295, 183, 202, 288, 16726, 52231, 473, 495, 69, 63, 16491, 38367,
    245, 259, 49158, 480, 470, 24941, 53254, 16426, 33855, 187, 16620, 46351, 434, 25048, 61709, 58, 16485, 38922,
    218, 305, 341, 468, 24955, 61961, 41, 115, 160, 197, 273, 16684, 51717, 499, 16778, 62559, 83, 46,
    105, 16592, 44335, 303, 386, 424, 16862, 62911, 1, 91, 16534, 38111, 229, 274, 302, 354, 392, 25022,
    53508, 72, 145, 16526, 41487, 282, 329, 419, 457, 479, 74, 148, 181, 217, 287, 337, 404, 25050,
    62730, 34, 92, 152, 193, 16606, 48143, 498, 377, 399, 51695, 57, 37900, 162, 199, 280, 16707, 51207,
    471, 24942, 64516, 7, 16459, 37263, 184, 250, 16673, 48607, 496, 486, 24957, 55302, 24, 128, 157, 24771,
    44038, 283, 331, 451, 25081, 59403, 22, 96, 139, 225, 238, 311, 368, 374, 16812, 52367, 67, 76,
    120, 16575, 39103, 277, 16704, 49410, 420, 25066, 56330, 48, 35343, 168, 247, 284, 332, 467, 16746, 53599,
    10, 116, 164, 216, 285, 334, 356, 16794, 63752, 40, 97, 126, 227, 256, 314, 448, 454, 16892,
    60815, 89, 131, 176, 214, 16645, 50447, 16837, 62468, 56623, 84, 77, 16490, 39439, 279, 325, 371, 409,
    431, 49, 43, 16502, 36063, 213, 258, 318, 370, 408, 25038, 54276, 20, 29, 103, 188, 252, 309,
    349, 485, 24940, 64007, 17, 35852, 161, 215, 281, 324, 355, 393, 415, 61935, 19, 59, 16518, 39951,
    262, 322, 482, 361, 383, 85, 16395, 32911, 165, 16616, 46095, 433, 455, 509, 55743, 87, 98, 158,
    243, 43009, 45571, 268, 333, 483, 24954, 55562, 53, 16497, 36991, 185, 203, 290, 343, 500, 16795, 51823,
    2, 12, 135, 16558, 43279, 321, 450, 488, 8559, 56577, 9, 99, 159, 244, 257, 315, 385, 391,
    16829, 63903, 55, 16412, 34159, 186, 204, 308, 347, 421, 16875, 58751, 54, 61, 119, 173, 205, 294,
    16734, 51343, 16842, 54367, 80, 34831, 166, 16633, 45103, 464, 423, 16861, 60575, 39, 112, 16525, 37599, 198,
    16644, 47727, 481, 360, 414, 64959, 86, 94, 156, 194, 16638, 45647, 401, 407, 25037, 59654, 23, 44,
    16492, 42255, 16649, 47279, 353, 502, 24973, 59910, 21, 45, 151, 189, 221, 310, 351, 501, 24956, 60679,
    65, 35087, 182, 201, 270, 339, 452, 16747, 63583, 8, 130, 127, 16580, 41167, 16660, 50191, 389, 25035,
    60424, 56, 114, 111, 212, 272, 298, 432, 438, 16876, 64143, 51, 144, 109, 226, 207, 312, 384,
    390, 16828, 57487, 32, 36111, 40971, 219, 306, 344, 357, 16811, 53375, 82, 62, 122, 16593, 43055, 45407,
    418, 456, 510, 59599, 88, 146, 143, 228, 44289, 275, 319, 402, 440, 16878, 56511, 16457, 33794, 147,
    163, 246, 264, 327, 387, 425, 447, 68, 14, 136, 190, 16621, 47375, 466, 16888, 55855, 33, 27,
    102, 172, 44159, 291, 345, 373, 16827, 55423, 4, 37127, 133, 171, 251, 292, 346, 405, 16859, 59775,
    90, 117, 169, 234, 304, 338, 436, 16890, 64607, 3, 60, 104, 16559, 39343, 267, 330, 435, 489,
    511};
void build_schedule(Params& prm, int pairs) {
  for (int i = 0; i < kAttnUnits; i++) prm.blk[i] = (uint16_t)(i | 1 << 12);
  uint8_t delay[kMaxPairs] = {};
  static uint16_t lists[kMaxPairs][kMaxUnits];
  int n[kMaxPairs] = {};
  double t[kMaxPairs] = {};
  const double ta = 40.0, to = 59.0;
  for (int u = 0; u < kUnits; u++) {
    int p = 0;
    for (int q = 1; q < pairs; q++)
      if (t[q] < t[p] - 1e-9) p = q;
    uint16_t code;
    if (u < kAttnUnits) {
      code = (uint16_t)u;
    } else {
      const int o = u - kAttnUnits, g2 = o / 5, r = o % 5;
      code = (uint16_t)(0x800F | (r < 4 ? ((2 * g2 + (r >> 1)) << 2) | (r & 1) : ((2 * g2) << 2) | 2) << 8);
    }
    lists[p][n[p]++] = code;
    t[p] += u < kAttnUnits ? ta : to;
  }
  if (pairs == kTunedPairs) {
    for (int p = 0, o = 0; p < pairs; p++) {
      n[p] = kTunedLen[p];
      delay[p] = kTunedDelay[p];
      for (int i = 0; i < n[p]; i++) lists[p][i] = kTunedUnit[o++];
    }
    for (int i = 0; i < kAttnUnits; i++) prm.blk[i] = kTunedBlock[i];
  }
  int o = 0;
  for (int p = 0; p < pairs; p++) {
    prm.head[p] = o | n[p] << 10 | delay[p] << 15 | (uint32_t)(lists[p][0] & 511) << 23;
    for (int i = 0; i < n[p]; i++) prm.unit[o++] = lists[p][i];
  }
}

}

extern "C" void kernel_launch(void* const* d_in, const int* in_sizes, int n_in, void* d_out, int out_size) {
  (void)in_sizes; (void)n_in; (void)out_size;
  void* fnp = nullptr;
  cudaDriverEntryPointQueryResult qr;
  if (cudaGetDriverEntryPoint("cuTensorMapEncodeTiled", &fnp, cudaEnableDefault, &qr) != cudaSuccess || !fnp) return;
  EncodeFn fn = (EncodeFn)fnp;
  void* optr = nullptr;
  cudaGetSymbolAddress(&optr, g_o);
  Params prm;
  bool ok = true;
  for (int br = 0; br < 2; br++) {
    void* const* in = d_in + 5 * br;
    ok &= encode_2d(fn, &prm.x[br], in[0], (uint64_t)kB * kSq, kD, NQ);
    ok &= encode_kv(fn, &prm.kv[br], in[1]);
    ok &= encode_kv(fn, &prm.kv[2 + br], in[2]);
    ok &= encode_panels(fn, &prm.wq[br], in[3], kD, kH * kDh, 64);
    ok &= encode_panels(fn, &prm.wo[br], in[4], kH * kDh, kD, 64);
    prm.xp[br] = (const __nv_bfloat16*)in[0];
    prm.wp[br] = (const __nv_bfloat16*)in[3];
    prm.kp[br] = (const __nv_bfloat16*)in[1];
    prm.vp[br] = (const __nv_bfloat16*)in[2];
  }
  prm.op = (__nv_bfloat16*)d_out;
  ok &= encode_2d(fn, &prm.o_ld, optr, (uint64_t)kAttnUnits * 4 * kSq, 64, NQ, CU_TENSOR_MAP_SWIZZLE_NONE);
  ok &= encode_panels(fn, &prm.out, d_out, (uint64_t)kB * kSq, 2 * kD, ST_ROWS, 1);
  if (!ok) return;
  cudaFuncSetAttribute(mha_fused_kernel, cudaFuncAttributeMaxDynamicSharedMemorySize, SMEM_BYTES);
  cudaLaunchConfig_t cfg = {};
  cfg.gridDim = dim3(2);
  cfg.blockDim = dim3(384);
  cfg.dynamicSmemBytes = SMEM_BYTES;
  cfg.stream = cudaStreamPerThread;
  int pairs = 0;
  if (cudaOccupancyMaxActiveClusters(&pairs, mha_fused_kernel, &cfg) != cudaSuccess || pairs < 1) return;
  if (pairs > kMaxPairs) pairs = kMaxPairs;
  if (pairs < 24) return;
  build_schedule(prm, pairs);
  mha_fused_kernel<<<2 * pairs, 384, SMEM_BYTES, cudaStreamPerThread>>>(prm);
}
```

```cpp
#include <cuda_runtime.h>
#include <cuda_bf16.h>
#include <cuda.h>
#include <stdint.h>

namespace {

constexpr int kB = 16, kSq = 224, kD = 640, kH = 32, kSk = 1024, kDh = 128;
constexpr int kGroups = 2 * kB;
constexpr int kAttnUnits = kGroups * kH / 2;
constexpr int kOutUnits = kGroups * 5 / 2;
constexpr int kUnits = kAttnUnits + kOutUnits;
constexpr int kMaxUnits = kUnits + 64;
constexpr int kMaxPairs = 72;
constexpr int NQ = 112;
constexpr int PANEL = NQ * 128;
constexpr float kQScale = 0.08838834764831845f * 1.4426950408889634f;
constexpr int SLOT = 16384;
constexpr int NSLOT = 7;

constexpr int SM_PANEL = 0;
constexpr int SM_RING = SM_PANEL + 8 * PANEL;
constexpr int NBAR = NSLOT + 8;
constexpr int SM_RCP = SM_RING + NSLOT * SLOT;
constexpr int SM_BAR = SM_RCP + 640;
constexpr int SM_END = SM_BAR + 8 * (2 * NBAR + 12) + 32;
constexpr int SMEM_BYTES = SM_END + 1024;
static_assert(SM_RING % 1024 == 0 && PANEL % 1024 == 0, "swizzle alignment");
static_assert(SMEM_BYTES <= 232448, "smem");

struct Params {
  CUtensorMap x[2], wq[2], kv[4], wo[2];
  CUtensorMap o_ld, out;
  const __nv_bfloat16* xp[2];
  const __nv_bfloat16* wp[2];
  const __nv_bfloat16* kp[2];
  const __nv_bfloat16* vp[2];
  __nv_bfloat16* op;
  uint32_t head[kMaxPairs];
  uint16_t unit[kMaxUnits];
  uint16_t blk[kAttnUnits];
};

struct Unit {
  bool attn, mc;
  int g, hc;
  int h0, nslab;
};
__device__ __forceinline__ int unit_slabs(uint32_t u) {
  return (u & 0x8000u) ? 4 * ((u & 15) + 1 - ((u >> 4) & 15)) : kD / 64;
}
__device__ __forceinline__ Unit decode_unit(uint32_t u, uint32_t rank) {
  Unit r;
  r.attn = !(u & 0x8000u);
  r.nslab = unit_slabs(u);
  if (r.attn) {
    r.g = (u >> 4) & 31;
    r.hc = (u & 15) * 2 + rank;
    r.mc = true;
    r.h0 = 0;
  } else {
    const uint32_t t = (u >> 8) & 3;
    r.mc = t < 2;
    r.g = ((u >> 10) & 31) + (t < 2 ? 0 : rank);
    r.hc = t < 2 ? 2 * t + rank : 4;
    r.h0 = (u >> 4) & 15;
  }
  return r;
}

__device__ uint4 g_qrow[2 * kMaxPairs * 2 * 16 * 128];
__device__ unsigned int g_pc[128 * 16 * 2];
__device__ __nv_bfloat16 g_o[(size_t)kAttnUnits * kSq * 2 * kDh];
__device__ unsigned int g_ticket;
__device__ unsigned int g_rd[kAttnUnits];
__device__ unsigned int g_cnt[kAttnUnits];

constexpr int CREGS = 232, SM_OFF = -2, Q_PIN = 0x15, ST_ROWS = 56;
template <bool V>
struct BoolC {
  static constexpr bool value = V;
};
template <int V>
struct IntC {
  static constexpr int value = V;
};
template <int I, int N, class F>
__device__ __forceinline__ void static_for(F&& f) {
  if constexpr (I < N) {
    f(IntC<I>{});
    static_for<I + 1, N>(f);
  }
}
constexpr uint32_t kPat0 = 04321432100, kPat1 = 04302102100;
__host__ __device__ constexpr int x_pos(int pat, int k) { return ((pat == 0 ? kPat0 : kPat1) >> 3 * k) & 7; }
__host__ __device__ constexpr int x_off(int pat, int k) { return k == 0 ? 0 : x_off(pat, k - 1) + (x_pos(pat, k - 1) == 0 ? 3 : 1); }
__host__ __device__ constexpr int w_cut(int i) { return 56 * i / 5; }
__device__ __forceinline__ uint32_t unit_pattern(uint32_t u, uint32_t prev) {
  return (prev & 0x8000u) && unit_slabs(u) >= 10 ? kPat1 : kPat0;
}
__device__ __forceinline__ uint32_t next_pos(uint32_t pos, int k, uint32_t pat) {
  return k < 9 ? (pat >> (3 * k + 3)) & 7 : (pos & 3) + 1;
}
__device__ __forceinline__ uint32_t pick(bool c, uint32_t a, uint32_t b) {
  uint32_t r;
  asm("{\n.reg .pred p;\nsetp.ne.u32 p, %1, 0;\nselp.u32 %0, %2, %3, p;\n}" : "=r"(r) : "r"((uint32_t)c), "r"(a), "r"(b));
  return r;
}
__device__ __forceinline__ uint32_t ring_round(uint32_t i) { return (i * 9363u) >> 16; }
__device__ __forceinline__ uint32_t ring_slot(uint32_t i) { return i - NSLOT * ring_round(i); }
__device__ __forceinline__ uint32_t ring_par(uint32_t i) { return ring_round(i) & 1; }

__device__ __forceinline__ uint32_t smem_u32(const void* p) { return (uint32_t)__cvta_generic_to_shared(p); }
__device__ __forceinline__ void mbar_init(uint32_t bar, uint32_t cnt) {
  asm volatile("mbarrier.init.shared::cta.b64 [%0], %1;" ::"r"(bar), "r"(cnt));
}
__device__ __forceinline__ void mbar_arrive1_if(uint32_t bar, bool pred) {
  asm volatile("{\n.reg .pred p;\nsetp.ne.u32 p, %1, 0;\n@p mbarrier.arrive.shared::cta.b64 _, [%0];\n}" ::"r"(bar), "r"((uint32_t)pred)
               : "memory");
}
__device__ __forceinline__ void mbar_wait_warp(uint32_t bar, uint32_t parity) {
  asm volatile(
      "{\n.reg .pred p, q;\n.reg .u32 c;\n"
      "mov.u32 c, 0;\n"
      "SPIN:\n"
      "mbarrier.try_wait.parity.shared::cta.b64 p, [%0], %1;\n"
      "vote.sync.all.pred q, p, 0xffffffff;\n"
      "@q bra.uni DONE;\n"
      "add.u32 c, c, 1;\n"
      "setp.gt.u32 q, c, 0x1000000;\n"
      "@q trap;\n"
      "bra.uni SPIN;\n"
      "DONE:\n}" ::"r"(bar),
      "r"(parity)
      : "memory");
}
__device__ __forceinline__ uint32_t mbar_test(uint32_t bar, uint32_t parity) {
  uint32_t ok;
  asm volatile(
      "{\n.reg .pred p;\nmbarrier.test_wait.parity.shared::cta.b64 p, [%1], %2;\nselp.u32 %0, 1, 0, p;\n}"
      : "=r"(ok)
      : "r"(bar), "r"(parity)
      : "memory");
  return ok;
}
__device__ __forceinline__ uint32_t mbar_test_if(uint32_t bar, uint32_t parity, bool pred) {
  uint32_t ok;
  asm volatile(
      "{\n.reg .pred p, q;\nsetp.ne.u32 q, %3, 0;\nsetp.eq.u32 p, %3, 0;\n"
      "@q mbarrier.test_wait.parity.shared::cta.b64 p, [%1], %2;\nselp.u32 %0, 1, 0, p;\n}"
      : "=r"(ok)
      : "r"(bar), "r"(parity), "r"((uint32_t)pred)
      : "memory");
  return ok;
}
#define ELECTED "{\n.reg .pred e;\nelect.sync _|e, 0xffffffff;\n@e "
constexpr uint64_t kEvictFirst = 0x12F0000000000000ull, kEvictNormal = 0x1000000000000000ull;
__device__ __forceinline__ void flag_wait(const unsigned int* p, uint32_t target) {
  asm volatile(
      "{\n.reg .pred p, q;\n.reg .u32 c, v;\n"
      "mov.u32 c, 0;\n"
      "SPIN:\n"
      "ld.acquire.gpu.global.u32 v, [%0];\n"
      "setp.ge.u32 p, v, %1;\n"
      "vote.sync.all.pred q, p, 0xffffffff;\n"
      "@q bra.uni DONE;\n"
      "nanosleep.u32 200;\n"
      "add.u32 c, c, 1;\n"
      "setp.gt.u32 q, c, 0x1000000;\n"
      "@q trap;\n"
      "bra.uni SPIN;\n"
      "DONE:\n}" ::"l"(p),
      "r"(target)
      : "memory");
}
__device__ __forceinline__ uint32_t flags_wait(const unsigned int* p, uint32_t target, uint32_t need) {
  uint32_t m;
  asm volatile(
      "{\n.reg .pred p, q;\n.reg .u32 c, v;\n"
      "mov.u32 c, 0;\n"
      "SPIN:\n"
      "ld.acquire.gpu.global.u32 v, [%1];\n"
      "setp.ge.u32 p, v, %2;\n"
      "vote.sync.ballot.b32 %0, p, 0xffffffff;\n"
      "and.b32 v, %0, %3;\n"
      "setp.eq.u32 q, v, %3;\n"
      "@q bra.uni DONE;\n"
      "add.u32 c, c, 1;\n"
      "setp.gt.u32 q, c, 0x1000000;\n"
      "@q trap;\n"
      "bra.uni SPIN;\n"
      "DONE:\n"
      "fence.proxy.async.global;\n}"
      : "=&r"(m)
      : "l"(p), "r"(target), "r"(need)
      : "memory");
  return m;
}
__device__ __forceinline__ void e_arrive(uint32_t bar, uint32_t n) {
  asm volatile(ELECTED "mbarrier.arrive.shared::cta.b64 _, [%0], %1;\n}" ::"r"(bar), "r"(n) : "memory");
}
__device__ __forceinline__ void e_expect_tx(uint32_t bar, uint32_t bytes) {
  asm volatile(ELECTED "mbarrier.arrive.expect_tx.shared::cta.b64 _, [%0], %1;\n}" ::"r"(bar), "r"(bytes) : "memory");
}
__device__ __forceinline__ void tma_ld2(uint32_t dst, const CUtensorMap* m, int c0, int c1, uint32_t bar, uint64_t pol) {
  asm volatile(ELECTED
               "cp.async.bulk.tensor.2d.shared::cluster.global.mbarrier::complete_tx::bytes.L2::cache_hint [%0], [%1, {%3, %4}], "
               "[%2], %5;\n}" ::"r"(dst),
               "l"(m), "r"(bar), "r"(c0), "r"(c1), "l"(pol)
               : "memory");
}
__device__ __forceinline__ void tma_ld2_mc(uint32_t dst, const CUtensorMap* m, int c0, int c1, uint32_t bar, uint64_t pol) {
  asm volatile(ELECTED
               "cp.async.bulk.tensor.2d.shared::cluster.global.mbarrier::complete_tx::bytes.multicast::cluster.L2::cache_hint "
               "[%0], [%1, {%3, %4}], [%2], %5, %6;\n}" ::"r"(dst),
               "l"(m), "r"(bar), "r"(c0), "r"(c1), "h"((uint16_t)3), "l"(pol)
               : "memory");
}
__device__ __forceinline__ void tma_ld3(uint32_t dst, const CUtensorMap* m, int c1, int c2, uint32_t bar, uint64_t pol) {
  asm volatile(ELECTED
               "cp.async.bulk.tensor.3d.shared::cluster.global.mbarrier::complete_tx::bytes.L2::cache_hint [%0], [%1, {%3, %4, "
               "%5}], [%2], %6;\n}" ::"r"(dst),
               "l"(m), "r"(bar), "r"(0), "r"(c1), "r"(c2), "l"(pol)
               : "memory");
}
__device__ __forceinline__ void tma_ld4(uint32_t dst, const CUtensorMap* m, int c3, uint32_t bar, uint64_t pol) {
  asm volatile(ELECTED
               "cp.async.bulk.tensor.4d.shared::cluster.global.mbarrier::complete_tx::bytes.L2::cache_hint [%0], [%1, {%3, %3, "
               "%3, %4}], [%2], %5;\n}" ::"r"(dst),
               "l"(m), "r"(bar), "r"(0), "r"(c3), "l"(pol)
               : "memory");
}
__device__ __forceinline__ void tma_st3(const CUtensorMap* m, int c1, int c2, uint32_t src, bool add) {
  if (add)
    asm volatile(ELECTED "cp.reduce.async.bulk.tensor.3d.global.shared::cta.add.bulk_group [%0, {%2, %3, %4}], [%1];\n}" ::"l"(m), "r"(src),
                 "r"(0), "r"(c1), "r"(c2)
                 : "memory");
  else
    asm volatile(ELECTED "cp.async.bulk.tensor.3d.global.shared::cta.bulk_group [%0, {%2, %3, %4}], [%1];\n}" ::"l"(m), "r"(src), "r"(0),
                 "r"(c1), "r"(c2)
                 : "memory");
}
__device__ __forceinline__ void wgmma_fence() { asm volatile("wgmma.fence.sync.aligned;" ::: "memory"); }
__device__ __forceinline__ void wgmma_commit() { asm volatile("wgmma.commit_group.sync.aligned;" ::: "memory"); }
template <int N>
__device__ __forceinline__ void wgmma_wait() {
  asm volatile("wgmma.wait_group.sync.aligned %0;" ::"n"(N) : "memory");
}
template <int N>
__device__ __forceinline__ void wgmma_wait_pin(int never, int c) {
  asm volatile("{\n.reg .pred p;\nsetp.eq.u32 p, %1, %2;\nAGAIN:\nwgmma.wait_group.sync.aligned %0;\n@p bra.uni AGAIN;\n}" ::"n"(N),
               "r"(never), "r"(c)
               : "memory");
}
__device__ __forceinline__ void pin_order(int never, int c) {
  asm volatile("{\n.reg .pred p;\nsetp.eq.u32 p, %0, %1;\nAGAIN:\n@p nanosleep.u32 1;\n@p bra.uni AGAIN;\n}" ::"r"(never), "r"(c) : "memory");
}
template <int N>
__device__ __forceinline__ void fence_regs(float (&d)[N]) {
#pragma unroll
  for (int i = 0; i < N; i++) asm volatile("" : "+f"(d[i])::"memory");
}
__device__ __forceinline__ void fence_async_smem() { asm volatile("fence.proxy.async.shared::cta;" ::: "memory"); }
__device__ __forceinline__ void bar_sync(int id, int n) { asm volatile("bar.sync %0, %1;" ::"r"(id), "r"(n) : "memory"); }
__device__ __forceinline__ void bar_arrive(int id, int n) {
  asm volatile("bar.arrive %0, %1;" ::"r"(id), "r"(n) : "memory");
}
__device__ __forceinline__ void stsm_x4_t(uint32_t addr, uint32_t r0, uint32_t r1, uint32_t r2, uint32_t r3) {
  asm volatile("stmatrix.sync.aligned.m8n8.x4.trans.shared.b16 [%0], {%1, %2, %3, %4};" ::"r"(addr), "r"(r0), "r"(r1),
               "r"(r2), "r"(r3)
               : "memory");
}
__device__ __forceinline__ void stsm_x4_t_pin(uint32_t addr, uint32_t r0, uint32_t r1, uint32_t r2, uint32_t r3, int never, int c) {
  asm volatile(
      "{\n.reg .pred p;\nsetp.eq.u32 p, %5, %6;\nAGAIN:\n"
      "stmatrix.sync.aligned.m8n8.x4.trans.shared.b16 [%0], {%1, %2, %3, %4};\n@p bra.uni AGAIN;\n}" ::"r"(addr),
      "r"(r0), "r"(r1), "r"(r2), "r"(r3), "r"(never), "r"(c)
      : "memory");
}
__device__ __forceinline__ uint32_t pack_bf16(float lo, float hi) {
  uint32_t r;
  asm("cvt.rn.bf16x2.f32 %0, %1, %2;" : "=r"(r) : "f"(hi), "f"(lo));
  return r;
}
__device__ __forceinline__ float ex2(float x) {
  float y;
  asm("ex2.approx.ftz.f32 %0, %1;" : "=f"(y) : "f"(x));
  return y;
}
__device__ __forceinline__ uint32_t mk_desc(uint32_t addr) { return (1u << 16) | ((addr & 0x3FFFFu) >> 4); }

template <int TA, int TB = 0, int KV = 0>
__device__ __forceinline__ void wgmma_n112(float (&d)[56], uint32_t descA, uint32_t descB, int scaleD) {
  asm volatile(
      "{\n.reg .pred p;\n.reg .b32 hi, hb;\n.reg .b64 da, db;\nsetp.ne.b32 p, %58, 0;\n"
      "mov.b32 hi, %62;\nmov.b32 hb, %61;\nmov.b64 da, {%56, hi};\nmov.b64 db, {%57, hb};\n"
      "wgmma.mma_async.sync.aligned.m64n112k16.f32.bf16.bf16 "
      "{%0, %1, %2, %3, %4, %5, %6, %7, %8, %9, %10, %11, %12, %13, "
      "%14, %15, %16, %17, %18, %19, %20, %21, %22, %23, %24, %25, %26, %27, "
      "%28, %29, %30, %31, %32, %33, %34, %35, %36, %37, %38, %39, %40, %41, "
      "%42, %43, %44, %45, %46, %47, %48, %49, %50, %51, %52, %53, %54, %55}, "
      "da, db, p, 1, 1, %59, %60;\n}\n"
      : "+f"(d[0]), "+f"(d[1]), "+f"(d[2]), "+f"(d[3]), "+f"(d[4]), "+f"(d[5]), "+f"(d[6]),
        "+f"(d[7]), "+f"(d[8]), "+f"(d[9]), "+f"(d[10]), "+f"(d[11]), "+f"(d[12]), "+f"(d[13]),
        "+f"(d[14]), "+f"(d[15]), "+f"(d[16]), "+f"(d[17]), "+f"(d[18]), "+f"(d[19]), "+f"(d[20]),
        "+f"(d[21]), "+f"(d[22]), "+f"(d[23]), "+f"(d[24]), "+f"(d[25]), "+f"(d[26]), "+f"(d[27]),
        "+f"(d[28]), "+f"(d[29]), "+f"(d[30]), "+f"(d[31]), "+f"(d[32]), "+f"(d[33]), "+f"(d[34]),
        "+f"(d[35]), "+f"(d[36]), "+f"(d[37]), "+f"(d[38]), "+f"(d[39]), "+f"(d[40]), "+f"(d[41]),
        "+f"(d[42]), "+f"(d[43]), "+f"(d[44]), "+f"(d[45]), "+f"(d[46]), "+f"(d[47]), "+f"(d[48]),
        "+f"(d[49]), "+f"(d[50]), "+f"(d[51]), "+f"(d[52]), "+f"(d[53]), "+f"(d[54]), "+f"(d[55])
      : "r"(descA), "r"(descB), "r"(scaleD), "n"(TA), "n"(TB), "n"(TB ? 8 : 0x40000040), "n"(KV ? 0x40000080 : 0x40000040));
}

template <int T>
__device__ __forceinline__ void pack_half(float (&pk)[56], const float (&a)[56]) {
#pragma unroll
  for (int i = 0; i < 28; i++) pk[28 * T + i] = __uint_as_float(pack_bf16(a[2 * i], a[2 * i + 1]));
}
template <int T>
__device__ __forceinline__ void fence_half(float (&pk)[56]) {
#pragma unroll
  for (int i = 0; i < 28; i++) asm volatile("" : "+f"(pk[28 * T + i])::"memory");
}
template <int T, int LO = 0, int HI = 7>
__device__ __forceinline__ void store_half(uint32_t addr, const float (&pk)[56]) {
#pragma unroll
  for (int q = LO; q < HI; q++) {
    const float* r = pk + 28 * T + 4 * q;
    stsm_x4_t(addr + T * PANEL + q * 2048, __float_as_uint(r[0]), __float_as_uint(r[1]), __float_as_uint(r[2]), __float_as_uint(r[3]));
  }
}

template <int T>
__device__ __forceinline__ void q_half(uint32_t addr, float (&pk)[56], const float (&a)[56], int never) {
#pragma unroll
  for (int q = 0; q < 7; q++) {
    uint32_t r[4];
#pragma unroll
    for (int i = 0; i < 4; i++) {
      r[i] = pack_bf16(a[8 * q + 2 * i] * kQScale, a[8 * q + 2 * i + 1] * kQScale);
      pk[28 * T + 4 * q + i] = __uint_as_float(r[i]);
    }
    if (q < 6 && (Q_PIN >> q & 1)) stsm_x4_t_pin(addr + T * PANEL + q * 2048, r[0], r[1], r[2], r[3], never, 32 + 2 * (7 * T + q));
    else stsm_x4_t(addr + T * PANEL + q * 2048, r[0], r[1], r[2], r[3]);
  }
}

__device__ __forceinline__ float bf_lo(uint32_t u) { return __uint_as_float(u << 16); }
__device__ __forceinline__ float bf_hi(uint32_t u) { return __uint_as_float(u & 0xFFFF0000u); }

__device__ __forceinline__ void fma8(float* o, float a, const uint4& w, float c) {
  o[0] = fmaf(a, bf_lo(w.x), o[0] * c), o[1] = fmaf(a, bf_hi(w.x), o[1] * c);
  o[2] = fmaf(a, bf_lo(w.y), o[2] * c), o[3] = fmaf(a, bf_hi(w.y), o[3] * c);
  o[4] = fmaf(a, bf_lo(w.z), o[4] * c), o[5] = fmaf(a, bf_hi(w.z), o[5] * c);
  o[6] = fmaf(a, bf_lo(w.w), o[6] * c), o[7] = fmaf(a, bf_hi(w.w), o[7] * c);
}
__device__ __forceinline__ void slow_rows(uint4* qrow, int tq, const __nv_bfloat16* xp, const __nv_bfloat16* wp,
                                          const __nv_bfloat16* kp, const __nv_bfloat16* vp, __nv_bfloat16* op) {
  if (tq >= NQ) return;
#pragma unroll 1
  for (int c = 0; c < 16; c++) {
    float q[8] = {};
#pragma unroll 1
    for (int k = 0; k < kD; k++)
      fma8(q, __bfloat162float(xp[tq * kD + k]), __ldg(reinterpret_cast<const uint4*>(wp + k * (kH * kDh)) + c), 1.f);
    qrow[c * 128] = make_uint4(pack_bf16(q[0] * kQScale, q[1] * kQScale), pack_bf16(q[2] * kQScale, q[3] * kQScale),
                               pack_bf16(q[4] * kQScale, q[5] * kQScale), pack_bf16(q[6] * kQScale, q[7] * kQScale));
  }
#pragma unroll 1
  for (int pass = 0; pass < 4; pass++) {
    float o[32] = {}, m = -INFINITY, l = 0.f;
#pragma unroll 1
    for (int key = 0; key < kSk; key++) {
      const uint4* kr = reinterpret_cast<const uint4*>(kp + key * kDh);
      const uint4* vr = reinterpret_cast<const uint4*>(vp + key * kDh) + 4 * pass;
      float s = 0.f;
#pragma unroll 1
      for (int c = 0; c < 16; c++) {
        const uint4 q = qrow[c * 128], k = __ldg(kr + c);
        s = fmaf(bf_lo(q.x), bf_lo(k.x), s); s = fmaf(bf_hi(q.x), bf_hi(k.x), s);
        s = fmaf(bf_lo(q.y), bf_lo(k.y), s); s = fmaf(bf_hi(q.y), bf_hi(k.y), s);
        s = fmaf(bf_lo(q.z), bf_lo(k.z), s); s = fmaf(bf_hi(q.z), bf_hi(k.z), s);
        s = fmaf(bf_lo(q.w), bf_lo(k.w), s); s = fmaf(bf_hi(q.w), bf_hi(k.w), s);
      }
      const float mn = fmaxf(m, s);
      const float ms = (mn == -INFINITY) ? 0.f : mn;
      const float corr = ex2(m - ms), p = ex2(s - ms);
      l = l * corr + p;
      m = mn;
      const float pb = __bfloat162float(__float2bfloat16(p));
#pragma unroll
      for (int c = 0; c < 4; c++) fma8(o + 8 * c, pb, __ldg(vr + c), corr);
    }
    const float sc = __fdividef(1.f, l);
    __nv_bfloat16* dst = op + (pass >> 1) * PANEL + (pass & 1) * 3584 + (tq >> 3) * 64 + (tq & 7);
#pragma unroll
    for (int d = 0; d < 32; d++) dst[(d >> 3) * 896 + (d & 7) * 8] = __float2bfloat16(o[d] * sc);
  }
}

__device__ __forceinline__ uint32_t launch_epoch() { return atomicAdd(&g_ticket, 1u) / gridDim.x; }

__global__ void __cluster_dims__(2, 1, 1) __launch_bounds__(384, 1) mha_fused_kernel(const __grid_constant__ Params prm) {
  extern __shared__ __align__(1024) unsigned char smem_raw[];

  const uint32_t sb = (smem_u32(smem_raw) + 1023u) & ~1023u;
  const uint32_t full0 = sb + SM_BAR, empty0 = full0 + 8 * NBAR, sfull0 = empty0 + 8 * NBAR;
  const uint32_t cred0 = sfull0 + 32, redo0 = cred0 + 64, epoch_addr = redo0 + 8, go_bar = redo0 + 16, ok_bar = redo0 + 24;
  const uint32_t rank = blockIdx.x & 1, pair = blockIdx.x >> 1;
  const uint32_t head = prm.head[pair];
  const int u_begin = head & 1023, u_end = u_begin + ((head >> 10) & 31);
  const uint32_t delay = ((head >> 15) & 255) * 256;
  const int tid = threadIdx.x;
  const int wid = __shfl_sync(0xffffffffu, tid >> 5, 0), wg = wid >> 2;

  if (wg == 2) {
    asm volatile("setmaxnreg.dec.sync.aligned.u32 %0;" ::"n"(504 - 2 * CREGS));
    const int warp = wid & 3, lane = tid & 31;
    bar_sync(0, 384);
    asm volatile("barrier.cluster.arrive.relaxed.aligned;" ::: "memory");
    if (warp < 3 && delay)
      asm volatile(
          "{\n.reg .pred p, q;\n.reg .u32 t0, t;\nmov.u32 t0, %%clock;\n"
          "SPIN:\nnanosleep.u32 100;\nmov.u32 t, %%clock;\nsub.u32 t, t, t0;\nsetp.lt.u32 p, t, %0;\n"
          "vote.sync.all.pred q, p, 0xffffffff;\n@q bra.uni SPIN;\n}" ::"r"(delay));
    auto slot_addr = [&](uint32_t i) { return sb + SM_RING + ring_slot(i) * SLOT; };
    auto full_bar = [&](uint32_t i) { return full0 + 8 * ring_slot(i); };
    const int count = (head >> 10) & 31;
    if (warp == 0) {
      uint32_t it = 6, prev = 0, code = head >> 23;
      auto acquire = [&](uint32_t i) { mbar_wait_warp(empty0 + 8 * ring_slot(i), ring_par(i) ^ 1); };
      uint32_t rblk = 0, rleft = 0;
      auto block_read = [&]() {
        asm volatile(ELECTED "red.relaxed.gpu.global.add.u32 [%0], 1;\n}" ::"l"(&g_rd[prm.blk[rblk] & 511]) : "memory");
        rblk++;
        rleft--;
      };
#pragma unroll 1
      for (int n = 1; n <= count; n++) {
        const uint32_t pat = unit_pattern(code, prev);
        const Unit u = decode_unit(code, rank);
        const int br = u.g >> 4;
        const CUtensorMap* mw = (u.attn ? prm.wq : prm.wo) + br;
        const int nslab = u.nslab;
#pragma unroll 1
        for (int k = n == 1 ? 2 : 0, pos = n == 1; k < nslab; k++) {
          const uint32_t i = it + (pos == 0);
          acquire(i);
          e_expect_tx(full_bar(i), SLOT);
          tma_ld3(slot_addr(i), mw, u.h0 * 256 + k * 64, u.hc * 2, full_bar(i), kEvictNormal);
          if (rleft && (k & 3) == 2 && k != 6) {
#pragma unroll 1
            do block_read();
            while (rleft && k == 2);
          }
          if (!u.attn && k == 4) rblk = u.g * 16 + u.h0, rleft = nslab >> 2;
          it = i + 1 + (pos == 0);
          pos = next_pos(pos, k, pat);
        }
        if (u.attn) {
          const int row0 = ((u.g & 15) * kH + u.hc) * kSk;
#pragma unroll 1
          for (int j = 0; j < kSk / 32; j++, it++) {
            acquire(it);
            e_expect_tx(full_bar(it), SLOT);
            const int isv = j == 31 || (j > 0 && !(j & 1));
            tma_ld4(slot_addr(it), &prm.kv[2 * isv + br], row0 / 8 + (((j + 1) >> 1) - isv) * 8, full_bar(it), kEvictFirst);
            if (j == kSk / 32 - 2) e_arrive(go_bar, 1);
          }
        }
        prev = code;
        code = prm.unit[u_begin + n];
      }
      if (rleft) {
        acquire(it + NSLOT - 1);
#pragma unroll 1
        while (rleft) block_read();
      }
    } else if (warp < 3) {
      asm volatile("barrier.cluster.wait.acquire.aligned;" ::: "memory");
      const int w = warp == 1 ? rank : rank ^ 1;
      uint32_t it = 6, nc = 0, pph = 0, go_ph = 0, prev = 0, code = head >> 23;
      uint32_t peer_cred0;
      asm("mapa.shared::cluster.u32 %0, %1, %2;" : "=r"(peer_cred0) : "r"(cred0), "r"(rank ^ 1));
#pragma unroll 1
      for (int n = 1; n <= count; n++) {
        const uint32_t pat = unit_pattern(code, prev);
        Unit u = decode_unit(code, rank);
        const CUtensorMap* mx = u.attn ? &prm.x[u.g >> 4] : &prm.o_ld;
        const int nslab = u.nslab;
        const bool polls = !u.attn && (warp == 1 || !u.mc);
        uint32_t done = 0, ready = 0;
        if (polls) {
          asm volatile("ld.volatile.shared.u32 %0, [%1];" : "=r"(done) : "r"(epoch_addr) : "memory");
          done *= 2;
        }
        const unsigned int* flags = g_cnt + u.g * 16 + (lane & 15);
        const uint64_t xpol = u.attn ? kEvictNormal : kEvictFirst;
        int xcol = n == 1 ? 128 : 0, xrow = (u.g & 15) * kSq + w * NQ;
#pragma unroll 1
        for (int k = n == 1 ? 2 : 0, pos = n == 1; k < nslab; k++) {
          if (polls && (k & 2) == 0) {
            const uint32_t hp = u.h0 + (k >> 2);
            if ((k & 1) == 0) {
              if (!(ready >> hp & 1)) ready = flags_wait(flags, done, 1u << hp);
              xrow = (prm.blk[u.g * 16 + hp] & 511) * (4 * kSq) + w * NQ;
            } else if (!(ready >> hp & 2)) {
              ready = flags_wait(flags, done, 0);
            }
          }
          const uint32_t i = it + 2 * w, q = pos - 1;
          const uint32_t fbar = full0 + 8 * (pos == 0 ? ring_slot(i) : NSLOT + 4 * w + q);
          const uint32_t dst = pos == 0 ? slot_addr(i) : sb + SM_PANEL + (4 * w + q) * PANEL;
          const uint32_t par = (pos == 0 ? ring_round(i) : pph >> q) & 1;
          pph ^= pos == 0 ? 0u : 1u << q;
          it += 1 + 2 * (pos == 0);
          pos = next_pos(pos, k, pat);
          mbar_wait_warp(fbar + 8 * NBAR, par ^ 1);
          e_expect_tx(fbar, PANEL);
          if (!u.mc) {
            tma_ld2(dst, mx, xcol, xrow, fbar, xpol);
          } else {
            if (warp == 1) {
              if (it > 10) mbar_wait_warp(cred0 + 8 * (nc & 7), (nc >> 3) & 1);
              tma_ld2_mc(dst, mx, xcol, xrow, fbar, xpol);
            } else if (it > 10) {
              asm volatile(ELECTED "mbarrier.arrive.shared::cluster.b64 _, [%0];\n}" ::"r"(peer_cred0 + 8 * (nc & 7)) : "memory");
            }
            nc += it > 10;
          }
          xcol += u.attn ? 64 : 0;
          xrow += u.attn ? 0 : kSq;
        }
        if (u.attn) {
          mbar_wait_warp(go_bar, go_ph);
          go_ph ^= 1;
          it += kSk / 32;
        }
        prev = code;
        code = prm.unit[u_begin + n];
      }
    } else {
      uint32_t epoch = 0, prev = 0;
      if (lane == 0) epoch = launch_epoch();
      epoch = __shfl_sync(0xffffffffu, epoch, 0);
      asm volatile("st.volatile.shared.u32 [%0], %1;" ::"r"(epoch_addr), "r"(epoch + 1) : "memory");
      auto publish = [&](unsigned int* p) {
        __syncwarp();
        asm volatile(ELECTED "red.release.gpu.global.add.u32 [%0], 1;\n}" ::"l"(p) : "memory");
      };
#pragma unroll 1
      for (int n = 0; n < count; n++) {
        const uint32_t code = prm.unit[u_begin + n], ph = n & 1;
        if (!(code & 0x8000u)) {
          const uint32_t blk = prm.blk[code & 511], gen = (blk >> 9) & 7;
          if (gen > 0) flag_wait(&g_rd[blk & 511], 5 * (epoch * (blk >> 12) + gen));
        }
        __syncwarp();
        e_arrive(ok_bar, 1);
        const bool clear = (code & 0xA000u) == 0x2000u;
        const uint32_t oc = clear ? prm.unit[u_begin + n + 1] : code;
        const Unit u = decode_unit(oc, rank);
        const int row = (u.g & 15) * kSq, cb = (u.g >> 4) * 10 + u.hc * 2;
        unsigned int* pc = g_pc + (oc >> 8 & 127) * 32 + rank;
        if (!(code & 0x8000u)) {
          if (clear) {
            uint4* o = reinterpret_cast<uint4*>(prm.op + (row + (lane >> 4)) * (2 * kD) + cb * 64) + (lane & 15);
#pragma unroll 1
            for (int r = 0; r < kSq / 2; r++, o += 4 * kD / 8) {
              *o = make_uint4(0, 0, 0, 0);
              __nanosleep(40);
            }
            publish(pc + 2 * (oc & 15));
          }
#pragma unroll 1
          for (int q = 0; q < 4; q++) mbar_wait_warp(sfull0 + 8 * q, ph);
          publish(&g_cnt[code & 511]);
        } else {
          const bool cleared = (prev & 0xA000u) == 0x2000u;
          if (u.h0) flag_wait(pc + 2 * (u.h0 - 1), epoch + 1);
          asm volatile("fence.proxy.async.global;" ::: "memory");
#pragma unroll 1
          for (int q = 0; q < 4; q++) {
            const int w = n + 1 < count ? q & 1 : q >> 1, t = n + 1 < count ? q >> 1 : q & 1;
            mbar_wait_warp(sfull0 + 8 * (2 * t + w), ph);
            fence_async_smem();
#pragma unroll 1
            for (int r = 0; r < NQ; r += ST_ROWS) {
              tma_st3(&prm.out, row + w * NQ + r, cb + t, sb + SM_PANEL + (4 * w + 2 + t) * PANEL + r * 128, u.h0 || cleared);
              asm volatile("cp.async.bulk.commit_group;" ::: "memory");
              if (n + 1 < count) asm volatile("cp.async.bulk.wait_group.read 0;" ::: "memory");
            }
            __syncwarp();
            e_arrive(empty0 + 8 * (NSLOT + 4 * w + 2 + t), 2);
          }
          if ((code & 15) != 15 && !cleared) {
            asm volatile("cp.async.bulk.wait_group 0;" ::: "memory");
            asm volatile("fence.proxy.async.global;" ::: "memory");
            publish(pc + 2 * (code & 15));
          }
        }
        prev = code;
      }
      asm volatile("cp.async.bulk.wait_group 0;" ::: "memory");
    }
  } else {
    const int tq = tid & 127, lane = tid & 31, warp = tq >> 5;
    if (tid == 0) {
#pragma unroll
      for (int i = 0; i < NBAR; i++) {
        mbar_init(full0 + 8 * i, 1);
        mbar_init(empty0 + 8 * i, 2);
      }
#pragma unroll
      for (int i = 0; i < 12; i++) mbar_init(sfull0 + 8 * i, i < 4 ? 4 : 1);
      mbar_init(go_bar, 1);
      mbar_init(ok_bar, 1);
      asm volatile("st.shared.v4.u32 [%0], {%1, %1, %1, %1};" ::"r"(redo0), "r"(0) : "memory");
      asm volatile("fence.mbarrier_init.release.cluster;" ::: "memory");
      fence_async_smem();
    }
    if (wid == 0) {
      __syncwarp();
      const Unit u = decode_unit(head >> 23, rank);
#pragma unroll
      for (int i = 0; i < 6; i++) {
        e_expect_tx(full0 + 8 * i, i % 3 == 1 ? SLOT : PANEL);
        if (i % 3 == 1) tma_ld3(sb + SM_RING + i * SLOT, &prm.wq[u.g >> 4], i / 3 * 64, u.hc * 2, full0 + 8 * i, kEvictNormal);
        else tma_ld2(sb + SM_RING + i * SLOT, &prm.x[u.g >> 4], i / 3 * 64, (u.g & 15) * kSq + i % 3 / 2 * NQ, full0 + 8 * i, kEvictNormal);
      }
    } else if (wid < 5) {
      asm volatile(ELECTED "prefetch.tensormap [%0];\n}" ::"l"(prm.x + 2 * (wid - 1) + (head >> 31)) : "memory");
    }
    bar_sync(0, 384);
    asm volatile("barrier.cluster.arrive.relaxed.aligned;" ::: "memory");
    asm volatile("setmaxnreg.inc.sync.aligned.u32 %0;" ::"n"(CREGS));
    const uint32_t stage = sb + SM_PANEL + wg * 4 * PANEL;
    const uint32_t st_q = __shfl_sync(
        0xffffffffu, stage + ((lane >> 4) * 8 + (lane & 7)) * 128 + (((2 * warp + ((lane >> 3) & 1)) ^ (lane & 7)) << 4), lane);
    const uint32_t st_p = st_q + 2 * PANEL;
    const uint32_t dq = mk_desc(stage), dring = mk_desc(sb + SM_RING);
    float acc[2][56], s[56] = {};
    const int never = (sb >> 24) & ~1u;
    uint32_t it = 0, pph = 0;
    auto wait_full = [&](uint32_t i) { mbar_wait_warp(full0 + 8 * ring_slot(i), ring_par(i)); };
    auto test = [&](uint32_t bar, uint32_t par) { return mbar_test_if(bar, par, warp == 0); };
    auto probe = [&](uint32_t i) { return test(full0 + 8 * ring_slot(i), ring_par(i)); };
    auto release = [&](uint32_t i) { mbar_arrive1_if(empty0 + 8 * ring_slot(i), tq == 0); };
    auto slot_desc = [&](uint32_t i) { return dring + ring_slot(i) * (SLOT >> 4); };
    if (wg == 1) bar_arrive(1, 256);

    struct Fin {
      uint32_t rp[16];
      char* dst;
    };
    uint32_t ps[14] = {};
    float l[28] = {};
    auto step_sums = [&]() {
#pragma unroll
      for (int g = 0; g < 14; g++) asm("add.rn.bf16x2 %0, %0, %1;" : "+r"(ps[g]) : "r"(pack_bf16(l[2 * g], l[2 * g + 1])));
#pragma unroll
      for (int q = 0; q < 3; q++) stsm_x4_t(st_p + q * 2048, ps[2 * q], ps[2 * q + 7], ps[2 * q + 1], ps[2 * q + 8]);
      asm volatile("stmatrix.sync.aligned.m8n8.x2.trans.shared.b16 [%0], {%1, %2};" ::"r"(st_p + 3 * 2048), "r"(ps[6]), "r"(ps[13])
                   : "memory");
    };
    auto flag_bad = [&](bool bad) {
      asm volatile("{\n.reg .pred p;\nsetp.ne.u32 p, %1, 0;\n@p st.shared.u32 [%0], %1;\n}" ::"r"(redo0 + 4 * wg), "r"((uint32_t)bad)
                   : "memory");
    };
    auto step_finite = [&](bool live) {
      uint32_t z[4] = {0, 0, 0, 0};
#pragma unroll
      for (int i = 0; i < 28; i++)
        asm volatile("fma.rn.bf16x2 %0, %1, %2, %0;" : "+r"(z[i & 3]) : "r"(__float_as_uint(s[2 * i])), "r"(__float_as_uint(s[2 * i + 1])));
      asm volatile("add.rn.bf16x2 %0, %0, %1;" : "+r"(z[0]) : "r"(z[1]));
      asm volatile("add.rn.bf16x2 %0, %0, %1;" : "+r"(z[2]) : "r"(z[3]));
      asm volatile("add.rn.bf16x2 %0, %0, %1;" : "+r"(z[0]) : "r"(z[2]));
      flag_bad(live && (((z[0] & 0x7F807F80u) + 0x00800080u) & 0x80008000u));
    };
    auto rows_addr = [&]() {
      const uint32_t q = min(tq, NQ - 1), hi = q >= 56, n = q - 56 * hi;
      return stage + 2 * PANEL + n * 128 + ((hi ^ (n & 7)) << 4);
    };
    auto rows_load = [&](Fin& f, uint32_t a) {
#pragma unroll
      for (int c = 0; c < 4; c++)
        asm volatile("ld.shared.v4.u32 {%0, %1, %2, %3}, [%4];"
                     : "=r"(f.rp[4 * c]), "=r"(f.rp[4 * c + 1]), "=r"(f.rp[4 * c + 2]), "=r"(f.rp[4 * c + 3])
                     : "r"(a ^ (c << 5))
                     : "memory");
    };
    auto step_rows = [&](const Fin& f, bool live) {
      const uint32_t q = min(tq, NQ - 1);
      float t = 0.f, t2 = 0.f;
#pragma unroll
      for (int i = 0; i < 8; i++) {
        uint32_t v;
        asm("add.rn.bf16x2 %0, %1, %2;" : "=r"(v) : "r"(f.rp[2 * i]), "r"(f.rp[2 * i + 1]));
        t += bf_lo(v), t2 += bf_hi(v);
      }
      t += t2;
      float r;
      asm("rcp.approx.ftz.f32 %0, %1;" : "=f"(r) : "f"(t));
      asm volatile("st.shared.u16 [%0], %1;" ::"r"(sb + SM_RCP + wg * 320 + (q >> 1 & 3) * 80 + (q >> 3) * 4 + (q & 1) * 2),
                   "h"((uint16_t)pack_bf16(r, r))
                   : "memory");
      flag_bad(live && !(t >= 9.094947017729282e-13f && t <= 1.329227995784916e36f));
    };
    auto step_scales = [&](Fin& f) {
#pragma unroll
      for (int c = 0; c < 4; c++)
        asm volatile("ld.shared.v4.u32 {%0, %1, %2, %3}, [%4];"
                     : "=r"(f.rp[4 * c]), "=r"(f.rp[4 * c + 1]), "=r"(f.rp[4 * c + 2]), "=r"(f.rp[4 * c + 3])
                     : "r"(sb + SM_RCP + wg * 320 + (lane & 3) * 80 + c * 16)
                     : "memory");
    };
    auto o_base = [&](uint32_t u) {
      return reinterpret_cast<char*>(g_o) + (size_t)((((prm.blk[u & 511] & 511u) * 4 + rank * 2) * 2 + wg) * (uint32_t)PANEL);
    };
    auto step_write = [&](const Fin& f, int lo, int hi) {
#pragma unroll
      for (int i = lo; i < hi; i++) {
        uint32_t v = __float_as_uint(s[i]);
        asm("mul.rn.bf16x2 %0, %0, %1;" : "+r"(v) : "r"(f.rp[(i % 28) >> 1]));
        s[i] = __uint_as_float(v);
        asm volatile("st.global.u32 [%0], %1;" ::"l"(f.dst + (i / 28) * 2 * PANEL + (i & 1) * 1792 + ((i % 28) >> 1) * 128), "r"(v) : "memory");
      }
    };
    auto keep_alive = [&](int lo, int hi, int c) {
      if (never == c) {
#pragma unroll
        for (int i = lo; i < hi; i++) asm volatile("st.shared.f32 [%0], %1;" ::"r"(stage + 4 * i), "f"(s[i]) : "memory");
        pin_order(never, c);
      }
    };
    auto step_signal = [&](int t) {
      __syncwarp();
      mbar_arrive1_if(sfull0 + 8 * (2 * t + wg), lane == 0);
    };
    auto free_panel = [&](int q) { mbar_arrive1_if(empty0 + 8 * (NSLOT + 4 * wg + q), tq < 2); };
    auto read_verdict = [&]() {
      uint32_t redo;
      asm volatile("ld.shared.u32 %0, [%1];" : "=r"(redo) : "r"(redo0 + 4 * wg) : "memory");
      return redo;
    };
    auto step_redo = [&](uint32_t prev) {
      asm volatile("" : "+r"(prev));
      bar_sync(3 + wg, 128);
      if (tq == 0) asm volatile("st.shared.u32 [%0], %1;" ::"r"(redo0 + 4 * wg), "r"(0) : "memory");
      const Unit u = decode_unit(prev & 511, rank);
      const int br = u.g >> 4, b = u.g & 15;
      const size_t off = (size_t)(b * kH + u.hc) * kSk * kDh;
      slow_rows(g_qrow + (blockIdx.x * 2 + wg) * (16 * 128) + tq, tq, prm.xp[br] + (b * kSq + wg * NQ) * kD, prm.wp[br] + u.hc * kDh,
                prm.kp[br] + off, prm.vp[br] + off, reinterpret_cast<__nv_bfloat16*>(o_base(prev)));
#pragma unroll
      for (int i = 0; i < 56; i++) s[i] = 0.f;
    };
    auto issue_slab = [&](uint32_t da, uint32_t db, int accum, auto split, auto tb) {
      constexpr int TB = tb.value, KS = TB ? 224 : 2;
      if (TB) db += 111 << 16;
      if (split.value == 1) {
#pragma unroll
        for (int t = 0; t < 2; t++) {
#pragma unroll
          for (int kk = 0; kk < 4; kk++) {
            if (t == 1 && kk == 2) bar_arrive(2 - wg, 256);
            wgmma_n112<1, 0, 1>(acc[t], da + t * 64 + kk * 256, db + kk * KS, 1);
          }
          wgmma_commit();
        }
      } else {
#pragma unroll
        for (int kk = 0; kk < 4; kk++) {
          if (kk == 3) bar_arrive(2 - wg, 256);
          wgmma_n112<1, TB>(acc[0], da + kk * 128, db + kk * KS, kk > 0 ? 1 : accum);
          wgmma_n112<1, TB>(acc[1], da + 512 + kk * 128, db + kk * KS, kk > 0 ? 1 : accum);
        }
        wgmma_commit();
      }
    };

    uint32_t code = head >> 23, prev = 0, pend = 0, uph = 0;
    uint32_t da = slot_desc(1), db = slot_desc(2 * wg);
    auto next_unit = [&](bool block) {
      da = slot_desc(it + 1), db = slot_desc(it + 2 * wg);
      if (block) {
        if (!__all_sync(0xffffffffu, probe(it + 1) & probe(it + 2 * wg))) {
          wait_full(it + 1);
          wait_full(it + 2 * wg);
        }
      }
    };
    wait_full(1);
    wait_full(2 * wg);
    for (int left = (head >> 10) & 31; left > 0; left--) {
      const int ui = u_end - left;
      uint32_t nxt;
      bool defer;
      auto peek = [&]() {
        const uint32_t cur = prm.unit[ui];
        nxt = __shfl_sync(0xffffffffu, (uint32_t)prm.unit[ui + 1], 0);
        defer = left > 1 && (!(nxt & 0x8000u) || ((cur & 0x8000u) ? unit_slabs(nxt) >= 10 : cur & 0x4000u));
      };
      const bool out = code & 0x8000u;
      uint32_t rel = 0;
      auto retire = [&]() {
        wgmma_wait<0>();
        fence_regs(acc[0]);
        fence_regs(acc[1]);
        mbar_arrive1_if(rel, rel);
        rel = 0;
      };
      auto turn = [&](int accum, auto mode, auto tb, auto first) {
        bar_sync(1 + wg, 256);
        if (!first.value) retire();
        wgmma_fence();
        issue_slab(da, db, accum, mode, tb);
      };
      auto take_turn = [&](int accum, auto mode, auto first) {
        if (out) turn(accum, mode, IntC<1>{}, first);
        else turn(accum, mode, IntC<0>{}, first);
      };
      Fin f;
      take_turn(0, IntC<0>{}, BoolC<true>{});
      int k = 0;
      const bool staged = pend == 2;
      if (out ? pend == 1 : !staged) {
        uint32_t redo = 0;
        static_for<0, 8>([&](auto kc) {
          constexpr int k = kc.value;
          if (k > 0) take_turn(1, IntC<0>{}, BoolC<false>{});
          if (k >= 4) keep_alive(w_cut(k - 4), w_cut(k - 3), 62 + 2 * k);
          if (k == 2) step_scales(f);
          constexpr int p0 = x_pos(0, k), p1 = x_pos(0, k + 1), o0 = x_off(0, k), o1 = x_off(0, k + 1);
          const uint32_t rw = empty0 + 8 * ring_slot(it + o0 + (p0 == 0));
          const uint32_t rx = empty0 + 8 * (p0 == 0 ? ring_slot(it + o0 + 2 * wg) : NSLOT + 4 * wg + p0 - 1);
          const uint32_t wi = it + o1 + (p1 == 0), xi = it + o1 + 2 * wg;
          const uint32_t xbar = full0 + 8 * (p1 == 0 ? ring_slot(xi) : NSLOT + 4 * wg + p1 - 1);
          const uint32_t xpar = (p1 == 0 ? ring_round(xi) : pph >> (p1 == 0 ? 0 : p1 - 1)) & 1;
          if constexpr (p1 != 0) pph ^= 1u << (p1 - 1);
          uint32_t okp = probe(wi) & test(xbar, xpar);
          if (k == 2) okp &= test(ok_bar, uph ^ pend);
          rel = pick(tq == 0, rw, pick(tq < 3 && (k < 6 || out), rx, 0));
          if (k == 0) {
            uint32_t a = rows_addr();
            asm volatile("" : "+r"(a), "+r"(okp), "+r"(rel));
            if (pend) step_sums();
            bar_sync(3 + wg, 128);
            rows_load(f, a);
          }
          if (k == 1) {
            mbar_arrive1_if(empty0 + 8 * (NSLOT + 4 * wg + 2), tq < 2 && pend);
            step_rows(f, pend);
          }
          if (k == 2) {
            step_finite(pend);
            f.dst = o_base(prev) + warp * 3584 + lane * 4;
          }
          if (k == 6) redo = read_verdict();
          if (k >= 3 && pend) step_write(f, w_cut(k - 3), w_cut(k - 2));
          if (k == 7) {
            if (__any_sync(0xffffffffu, redo)) step_redo(prev);
            __syncwarp();
            mbar_arrive1_if(sfull0 + 8 * (2 * lane + wg), lane < 2 && pend);
          }
          const bool ok = __all_sync(0xffffffffu, okp);
          da = slot_desc(wi);
          db = p1 == 0 ? slot_desc(xi) : dq + (p1 - 1) * (PANEL >> 4);
          if (!ok) {
            retire();
            wait_full(wi);
            mbar_wait_warp(xbar, xpar);
            if (k == 2) mbar_wait_warp(ok_bar, uph ^ pend);
          }
        });
        k = 8;
        if (out) turn(1, IntC<0>{}, IntC<1>{}, BoolC<false>{});
      }
      const int nslab = unit_slabs(code);
      uint32_t pos = k ? 3 : 0, wi = it + (k ? 12 : 1), xbar = full0 + 8 * (k ? NSLOT + 4 * wg + 2 : ring_slot(it + 2 * wg));
      const int kend = nslab - 2;
      if (k < kend) {
        uint32_t r = it + (k ? 13 : 3);
        const uint32_t pat = staged ? kPat1 : kPat0;
        const uint32_t keep_pos = out ? 3 : 1;
        const int keep_k = out ? nslab - 4 : 5;
#pragma unroll 1
        while (true) {
          rel = pick(tq == 0, empty0 + 8 * ring_slot(wi), pick(tq < 3 && (pos < keep_pos || k < keep_k), xbar + 8 * NBAR, 0));
          pos = next_pos(pos, k, pat);
          const bool ring = pos == 0;
          const uint32_t i = r + 2 * wg, q = pos - 1;
          wi = ring ? r + 1 : r;
          xbar = full0 + 8 * (ring ? ring_slot(i) : NSLOT + 4 * wg + q);
          const uint32_t xpar = (ring ? ring_round(i) : pph >> q) & 1;
          da = slot_desc(wi);
          db = ring ? slot_desc(i) : dq + q * (PANEL >> 4);
          pph ^= ring ? 0u : 1u << q;
          r += ring ? 3 : 1;
          const bool ok = __all_sync(0xffffffffu, probe(wi) & test(xbar, xpar));
          if (staged && k < 2) {
            if (k == 0) {
              store_half<1, 0, 4>(st_p, s);
            } else {
              store_half<1, 4, 7>(st_p, s);
              step_signal(1);
            }
          }
          if (!ok) {
            retire();
            wait_full(wi);
            mbar_wait_warp(xbar, xpar);
          }
          if (++k == kend) break;
          take_turn(1, IntC<0>{}, BoolC<false>{});
        }
      }
      it += nslab + (staged ? 8 : 4);
      const uint32_t ql = out ? 1 : 3, xl = full0 + 8 * (NSLOT + 4 * wg + ql), pl = pph >> ql & 1, dl = slot_desc(it - 1);
      pph ^= 1u << ql;
      if (!__all_sync(0xffffffffu, probe(it - 1) & test(xl, pl))) {
        retire();
        wait_full(it - 1);
        mbar_wait_warp(xl, pl);
      }
      auto last_turn = [&](auto tb) {
        constexpr int TB = tb.value;
        bar_sync(1 + wg, 256);
        retire();
        wgmma_fence();
#pragma unroll
        for (int t = 0; t < 2; t++) {
#pragma unroll
          for (int kk = 0; kk < 8; kk++)
            wgmma_n112<1, TB>(acc[t], (kk < 4 ? da : dl) + t * 512 + (kk & 3) * 128,
                              db + t * never + (TB ? 111 << 16 : 0) + (kk >> 2) * (PANEL >> 4) + (kk & 3) * (TB ? 224 : 2), 1);
          wgmma_commit();
        }
        bar_arrive(2 - wg, 256);
      };
      const uint32_t rw2 = empty0 + 8 * pick(tq == 0, ring_slot(it - 2), ring_slot(it - 1));
      if (!out) {
        {
          last_turn(IntC<0>{});
          keep_alive(28, 56, 80);
          const bool ok = __all_sync(0xffffffffu, probe(it));
          rel = pick(tq < 2, rw2, 0);
          da = slot_desc(it);
          wgmma_wait<1>();
          fence_regs(acc[0]);
          q_half<0>(st_q, s, acc[0], never);
          wgmma_wait<0>();
          fence_regs(acc[1]);
          q_half<1>(st_q, s, acc[1], never);
          mbar_arrive1_if(rel, rel);
          if (!ok) wait_full(it);
        }
        fence_async_smem();
        auto issue_s = [&](uint32_t dk, int accum) {
          wgmma_fence();
#pragma unroll
          for (int kk = 0; kk < 8; kk++)
            wgmma_n112<0, 0, 1>(s, dk + (kk >> 2) * 64 + (kk & 3) * 2, dq + (kk >> 2) * (PANEL >> 4) + (kk & 3) * 2, kk > 0 ? 1 : accum);
          wgmma_commit();
        };
        auto add_sums = [&]() {
#pragma unroll
          for (int jj = 0; jj < 14; jj++)
            asm volatile("{\n.reg .b32 t;\nshl.b32 t, %2, 16;\nadd.f32 %0, %0, t;\nand.b32 t, %2, 0xffff0000;\nadd.f32 %1, %1, t;\n}"
                         : "+f"(l[2 * jj]), "+f"(l[2 * jj + 1])
                         : "r"(ps[jj]));
        };
        auto softmax = [&](uint32_t par, int pin0) {
          const uint32_t pa = st_p + par * PANEL;
#pragma unroll
          for (int i = 0; i < 8 + SM_OFF; i++) s[i] = ex2(s[i]);
#pragma unroll
          for (int jj = 0; jj < 7; jj++) {
            const float* e = s + 8 * jj;
#pragma unroll
            for (int i = 8 * jj + 8 + SM_OFF; i < 8 * jj + 16 + SM_OFF; i++)
              if (i < 56) s[i] = ex2(s[i]);
            const uint32_t p0 = pack_bf16(e[0], e[1]), p1 = pack_bf16(e[2], e[3]), p2 = pack_bf16(e[4], e[5]), p3 = pack_bf16(e[6], e[7]);
            stsm_x4_t_pin(pa + jj * 2048, p0, p1, p2, p3, never, pin0);
            asm("add.rn.bf16x2 %0, %1, %2;" : "=r"(ps[2 * jj]) : "r"(p0), "r"(p1));
            asm("add.rn.bf16x2 %0, %1, %2;" : "=r"(ps[2 * jj + 1]) : "r"(p2), "r"(p3));
          }
        };
        bar_sync(1 + wg, 256);
        issue_s(da, never);
        bar_arrive(2 - wg, 256);
        {
#pragma unroll
          for (int i = 0; i < 28; i++) asm volatile("mov.b32 %0, 0;" : "=f"(l[i]));
          peek();
          const bool ok = __all_sync(0xffffffffu, probe(it + 1));
          da = slot_desc(it + 1);
          wgmma_wait_pin<0>(never, 180);
          fence_regs(s);
          release(it);
          softmax(0, 176);
          if (!ok) wait_full(it + 1);
        }
        it += 1;
#pragma unroll 1
        for (int j = 1; j < 16; j++) {
          fence_async_smem();
          bar_sync(1 + wg, 256);
          issue_s(da, 0);
          pin_order(never, 2 * j + 128);
          const uint32_t okv = mbar_test(full0 + 8 * ring_slot(it + 1), ring_par(it + 1));
          const uint32_t okk = probe(it + 2);
          da = slot_desc(it + 2);
          add_sums();
          const bool ok = __all_sync(0xffffffffu, okk);
          if (!__all_sync(0xffffffffu, okv)) wait_full(it + 1);
          {
            const uint32_t dv = slot_desc(it + 1), dp = dq + (3 - (j & 1)) * (PANEL >> 4);
            wgmma_fence();
#pragma unroll
            for (int kk = 0; kk < 4; kk++) {
              wgmma_n112<1, 0, 1>(acc[0], dv + kk * 256, dp + kk * 2, kk > 0 ? 1 : j > 1);
              wgmma_n112<1, 0, 1>(acc[1], dv + 64 + kk * 256, dp + kk * 2, kk > 0 ? 1 : j > 1);
            }
          }
          wgmma_commit();
          bar_arrive(2 - wg, 256);
          wgmma_wait<1>();
          fence_regs(s);
          release(it);
          softmax(j & 1, 2 * j + 192);
          wgmma_wait<0>();
          fence_regs(acc[0]);
          fence_regs(acc[1]);
          release(it + 1);
          it += 2;
          if (!ok) {
            wait_full(it);
          }
        }
        it += 1;
        fence_async_smem();
        bar_sync(1 + wg, 256);
        wgmma_fence();
        issue_slab(da, dq + 3 * (PANEL >> 4), 1, IntC<1>{}, IntC<0>{});
        pin_order(never, 182);
        mbar_arrive1_if(empty0 + 8 * (NSLOT + 4 * wg + (tq >> 1)), tq < 4);
        rel = pick(tq == 0, empty0 + 8 * ring_slot(it - 1), pick(tq < 3, empty0 + 8 * (NSLOT + 4 * wg + 3), 0));
        next_unit(defer);
        if (defer) {
          wgmma_wait<1>();
          fence_regs(acc[0]);
          pack_half<0>(s, acc[0]);
          fence_half<0>(s);
          wgmma_wait_pin<0>(never, 172);
          fence_regs(acc[1]);
          mbar_arrive1_if(rel, rel);
          pack_half<1>(s, acc[1]);
        }
        pend = 1;
      } else {
        last_turn(IntC<1>{});
        pin_order(never, 186);
        peek();
#pragma unroll
        for (int i = 0; i < 28; i++) ps[i >> 1] = 0, l[i] = 0.f;
        mbar_wait_warp(ok_bar, uph);
        next_unit(defer);
        rel = pick(tq < 2, rw2, pick(tq < 6, empty0 + 8 * (NSLOT + 4 * wg - 1 + (tq >> 1)), 0));
        wgmma_wait<1>();
        fence_regs(acc[0]);
        pack_half<0>(s, acc[0]);
        store_half<0>(st_p, s);
        step_signal(0);
        wgmma_wait<0>();
        fence_regs(acc[1]);
        mbar_arrive1_if(rel, rel);
        pack_half<1>(s, acc[1]);
        pend = 2;
      }
      if (!defer) {
        if (pend == 2) {
          store_half<1>(st_p, s);
        } else {
          step_sums();
          bar_sync(3 + wg, 128);
          rows_load(f, rows_addr());
          f.dst = o_base(code) + warp * 3584 + lane * 4;
          mbar_wait_warp(ok_bar, uph);
          step_rows(f, true);
          bar_sync(3 + wg, 128);
          step_scales(f);
          free_panel(2);
          retire();
          pack_half<0>(s, acc[0]);
          pack_half<1>(s, acc[1]);
          step_finite(true);
          step_write(f, 0, 28);
          bar_sync(3 + wg, 128);
          const uint32_t redo = read_verdict();
          step_write(f, 28, 56);
          if (__any_sync(0xffffffffu, redo)) step_redo(code);
          step_signal(0);
        }
        step_signal(1);
        pend = 0;
#pragma unroll
        for (int i = 0; i < 28; i++) ps[i >> 1] = 0, l[i] = 0.f;
        if (left > 1) {
          wait_full(it + 1);
          wait_full(it + 2 * wg);
        }
      }
      prev = code, code = nxt, uph ^= 1;
    }
    if (wg == 0) bar_sync(1, 256);
  }
}

typedef CUresult (*EncodeFn)(CUtensorMap*, CUtensorMapDataType, cuuint32_t, void*, const cuuint64_t*, const cuuint64_t*,
                             const cuuint32_t*, const cuuint32_t*, CUtensorMapInterleave, CUtensorMapSwizzle,
                             CUtensorMapL2promotion, CUtensorMapFloatOOBfill);

bool encode(EncodeFn fn, CUtensorMap* m, const void* ptr, int rank, const cuuint64_t* dims, const cuuint64_t* strides,
            const cuuint32_t* box, CUtensorMapL2promotion promo, CUtensorMapSwizzle swz = CU_TENSOR_MAP_SWIZZLE_128B) {
  const cuuint32_t es[4] = {1, 1, 1, 1};
  return fn(m, CU_TENSOR_MAP_DATA_TYPE_BFLOAT16, rank, const_cast<void*>(ptr), dims, strides, box, es,
            CU_TENSOR_MAP_INTERLEAVE_NONE, swz, promo,
            CU_TENSOR_MAP_FLOAT_OOB_FILL_NONE) == CUDA_SUCCESS;
}
bool encode_panels(EncodeFn fn, CUtensorMap* m, const void* ptr, uint64_t rows, uint64_t cols, uint32_t box_rows,
                   uint32_t box_blocks = 2) {
  const cuuint64_t dims[3] = {64, rows, cols / 64};
  const cuuint64_t strides[2] = {cols * 2, 128};
  const cuuint32_t box[3] = {64, box_rows, box_blocks};
  CUtensorMapL2promotion promo = CU_TENSOR_MAP_L2_PROMOTION_L2_128B;
  return encode(fn, m, ptr, 3, dims, strides, box, promo);
}
bool encode_kv(EncodeFn fn, CUtensorMap* m, const void* ptr) {
  const cuuint64_t dims[4] = {64, 8, 2, (uint64_t)kB * kH * kSk / 8};
  const cuuint64_t strides[3] = {kDh * 2, 128, 8 * kDh * 2};
  const cuuint32_t box[4] = {64, 8, 2, 8};
  CUtensorMapL2promotion promo = CU_TENSOR_MAP_L2_PROMOTION_L2_128B;
  return encode(fn, m, ptr, 4, dims, strides, box, promo);
}
bool encode_2d(EncodeFn fn, CUtensorMap* m, const void* ptr, uint64_t rows, uint64_t cols, uint32_t box_rows,
               CUtensorMapSwizzle swz = CU_TENSOR_MAP_SWIZZLE_128B) {
  const cuuint64_t dims[2] = {cols, rows};
  const cuuint64_t strides[1] = {cols * 2};
  const cuuint32_t box[2] = {64, box_rows};
  CUtensorMapL2promotion promo = CU_TENSOR_MAP_L2_PROMOTION_L2_128B;
  return encode(fn, m, ptr, 2, dims, strides, box, promo, swz);
}

constexpr int kTunedPairs = 66;
const uint16_t kTunedBlock[kAttnUnits] = {
    20480, 20486, 20492, 20498, 20504, 20510, 20516, 20522, 20528, 20534, 16444, 16450, 16456, 16462, 20996, 21002,
    20481, 20487, 20493, 20499, 20505, 20511, 20517, 20523, 20529, 20535, 16445, 16451, 16457, 16463, 20997, 21003,
    20482, 20488, 20494, 20500, 20506, 20512, 20518, 20524, 20530, 20536, 16446, 16452, 16458, 20992, 20998, 21004,
    20483, 20489, 20495, 20501, 20507, 20513, 20519, 20525, 20531, 20537, 16447, 16453, 16459, 20993, 20999, 21005,
    20484, 20490, 20496, 20502, 20508, 20514, 20520, 20526, 20532, 20538, 16448, 16454, 16460, 20994, 21000, 21006,
    20485, 20491, 20497, 20503, 20509, 20515, 20521, 20527, 20533, 20539, 16449, 16455, 16461, 20995, 21001, 21007,
    21008, 21012, 21016, 21020, 21024, 21028, 21032, 21036, 21040, 21044, 21048, 16956, 16960, 16964, 16968, 16972,
    21009, 21013, 21017, 21021, 21025, 21029, 21033, 21037, 21041, 21045, 21049, 16957, 16961, 16965, 16969, 16973,
    21010, 21014, 21018, 21022, 21026, 21030, 21034, 21038, 21042, 21046, 21050, 16958, 16962, 16966, 16970, 16974,
    21011, 21015, 21019, 21023, 21027, 21031, 21035, 21039, 21043, 21047, 21051, 16959, 16963, 16967, 16971, 16975,
    21504, 21506, 21508, 21510, 21512, 21514, 21516, 21518, 21520, 21522, 21524, 21526, 21528, 21530, 21532, 21534,
    21505, 21507, 21509, 21511, 21513, 21515, 21517, 21519, 21521, 21523, 21525, 21527, 21529, 21531, 21533, 21535,
    21536, 21540, 21544, 21548, 21552, 21556, 21560, 17468, 17472, 17476, 17480, 17484, 22016, 22020, 22024, 22028,
    21537, 21541, 21545, 21549, 21553, 21557, 21561, 17469, 17473, 17477, 17481, 17485, 22017, 22021, 22025, 22029,
    21538, 21542, 21546, 21550, 21554, 21558, 21562, 17470, 17474, 17478, 17482, 17486, 22018, 22022, 22026, 22030,
    21539, 21543, 21547, 21551, 21555, 21559, 21563, 17471, 17475, 17479, 17483, 17487, 22019, 22023, 22027, 22031,
    22032, 22034, 22036, 22038, 22040, 22042, 22044, 22046, 22048, 22050, 22052, 22054, 22056, 22058, 22060, 22062,
    22033, 22035, 22037, 22039, 22041, 22043, 22045, 22047, 22049, 22051, 22053, 22055, 22057, 22059, 22061, 22063,
    22064, 22066, 22068, 22070, 22072, 22074, 17980, 17982, 17984, 17986, 17988, 17990, 17992, 17994, 17996, 17998,
    22065, 22067, 22069, 22071, 22073, 22075, 17981, 17983, 17985, 17987, 17989, 17991, 17993, 17995, 17997, 17999,
    22528, 22529, 22530, 22531, 22532, 22533, 22534, 22535, 22536, 22537, 22538, 22539, 22540, 22541, 22542, 22543,
    22544, 22545, 22546, 22547, 22548, 22549, 22550, 22551, 22552, 22553, 22554, 22555, 22556, 22557, 22558, 22559,
    22560, 22570, 22580, 4178, 4188, 4198, 4208, 4218, 4228, 4238, 4248, 4258, 4268, 4278, 4288, 4298,
    22561, 22571, 22581, 4179, 4189, 4199, 4209, 4219, 4229, 4239, 4249, 4259, 4269, 4279, 4289, 4299,
    22562, 22572, 22582, 4180, 4190, 4200, 4210, 4220, 4230, 4240, 4250, 4260, 4270, 4280, 4290, 4300,
    22563, 22573, 22583, 4181, 4191, 4201, 4211, 4221, 4231, 4241, 4251, 4261, 4271, 4281, 4291, 4301,
    22564, 22574, 22584, 4182, 4192, 4202, 4212, 4222, 4232, 4242, 4252, 4262, 4272, 4282, 4292, 4302,
    22565, 22575, 22585, 4183, 4193, 4203, 4213, 4223, 4233, 4243, 4253, 4263, 4273, 4283, 4293, 4303,
    22566, 22576, 22586, 4184, 4194, 4204, 4214, 4224, 4234, 4244, 4254, 4264, 4274, 4284, 4294, 4304,
    22567, 22577, 22587, 4185, 4195, 4205, 4215, 4225, 4235, 4245, 4255, 4265, 4275, 4285, 4295, 4305,
    22568, 22578, 4176, 4186, 4196, 4206, 4216, 4226, 4236, 4246, 4256, 4266, 4276, 4286, 4296, 4306,
    22569, 22579, 4177, 4187, 4197, 4207, 4217, 4227, 4237, 4247, 4257, 4267, 4277, 4287, 4297, 4307};
const uint8_t kTunedLen[kTunedPairs] = {
    10, 10, 10, 10, 10, 10, 10, 9, 9, 11, 9, 11, 10, 10, 10, 10, 8, 9, 11, 8, 9, 10, 10, 11, 9, 9, 10, 10, 11, 10, 10, 11, 9,
    9, 10, 9, 9, 11, 10, 10, 9, 10, 11, 10, 10, 10, 10, 10, 9, 11, 10, 10, 10, 9, 10, 10, 10, 9, 10, 11, 10, 9, 10, 10, 9, 10};
const uint8_t kTunedDelay[kTunedPairs] = {
    0, 0, 0, 0, 0, 29, 5, 0, 105, 1, 0, 0, 1, 0, 1, 0, 0, 0, 0, 109, 109, 29,
    0, 0, 15, 111, 0, 31, 3, 7, 1, 0, 0, 105, 7, 72, 0, 0, 0, 0, 0, 1, 7, 0,
    0, 23, 5, 1, 0, 3, 1, 3, 0, 0, 7, 13, 0, 0, 0, 17, 35, 0, 0, 0, 115, 0};
const uint16_t kTunedUnit[] = {
    0, 37388, 178, 231, 266, 328, 403, 441, 8655, 55809, 50, 47, 140, 242, 239, 313, 416, 422,
    16860, 58511, 37, 93, 123, 210, 223, 297, 400, 406, 25036, 58375, 81, 95, 16508, 39177, 220, 293,
    348, 437, 16891, 60031, 52, 30, 153, 240, 24782, 48396, 417, 439, 16877, 62127, 25, 36870, 149, 170,
    235, 16691, 49471, 375, 25005, 61445, 71, 34053, 100, 179, 200, 269, 336, 388, 25018, 64778, 64, 38156,
    177, 230, 263, 16710, 51469, 54538, 53767, 26, 132, 180, 248, 286, 335, 372, 25002, 57866, 70, 129,
    110, 211, 255, 45057, 317, 497, 376, 16814, 58047, 18, 32775, 16509, 40207, 16662, 49679, 469, 16780, 53903,
    5, 31, 154, 16625, 43522, 47113, 301, 465, 503, 16782, 54719, 38, 13, 121, 224, 253, 295, 352,
    358, 24988, 57351, 36, 79, 16539, 41999, 45316, 16680, 49279, 484, 16779, 61551, 6, 78, 137, 192, 43583,
    316, 449, 487, 24958, 63492, 35, 15, 16522, 41231, 47621, 299, 369, 359, 24989, 58630, 16, 33039, 167,
    233, 271, 16724, 52495, 57615, 66, 33295, 183, 202, 288, 16726, 52231, 473, 495, 69, 63, 16491, 38367,
    245, 259, 49158, 480, 470, 24941, 53254, 16426, 33855, 187, 16620, 46351, 434, 25048, 61709, 58, 16485, 38922,
    218, 305, 341, 468, 24955, 61961, 41, 115, 160, 197, 273, 16684, 51717, 499, 16778, 62559, 83, 46,
    105, 16592, 44335, 303, 386, 424, 16862, 62911, 1, 91, 16534, 38111, 229, 274, 302, 354, 392, 25022,
    53508, 72, 145, 16526, 41487, 282, 329, 419, 457, 479, 74, 148, 181, 217, 287, 337, 404, 25050,
    62730, 34, 92, 152, 193, 16606, 48143, 498, 377, 399, 51695, 57, 37900, 162, 199, 280, 16707, 51207,
    471, 24942, 64516, 7, 16459, 37263, 184, 250, 16673, 48607, 496, 486, 24957, 55302, 24, 128, 157, 24771,
    44038, 283, 331, 451, 25081, 59403, 22, 96, 139, 225, 238, 311, 368, 374, 16812, 52367, 67, 76,
    120, 16575, 39103, 277, 16704, 49410, 420, 25066, 56330, 48, 35343, 168, 247, 284, 332, 467, 16746, 53599,
    10, 116, 164, 216, 285, 334, 356, 16794, 63752, 40, 97, 126, 227, 256, 314, 448, 454, 16892,
    60815, 89, 131, 176, 214, 16645, 50447, 16837, 62468, 56623, 84, 77, 16490, 39439, 279, 325, 371, 409,
    431, 49, 43, 16502, 36063, 213, 258, 318, 370, 408, 25038, 54276, 20, 29, 103, 188, 252, 309,
    349, 485, 24940, 64007, 17, 35852, 161, 215, 281, 324, 355, 393, 415, 61935, 19, 59, 16518, 39951,
    262, 322, 482, 361, 383, 85, 16395, 32911, 165, 16616, 46095, 433, 455, 509, 55743, 87, 98, 158,
    243, 43009, 45571, 268, 333, 483, 24954, 55562, 53, 16497, 36991, 185, 203, 290, 343, 500, 16795, 51823,
    2, 12, 135, 16558, 43279, 321, 450, 488, 8559, 56577, 9, 99, 159, 244, 257, 315, 385, 391,
    16829, 63903, 55, 16412, 34159, 186, 204, 308, 347, 421, 16875, 58751, 54, 61, 119, 173, 205, 294,
    16734, 51343, 16842, 54367, 80, 34831, 166, 16633, 45103, 464, 423, 16861, 60575, 39, 112, 16525, 37599, 198,
    16644, 47727, 481, 360, 414, 64959, 86, 94, 156, 194, 16638, 45647, 401, 407, 25037, 59654, 23, 44,
    16492, 42255, 16649, 47279, 353, 502, 24973, 59910, 21, 45, 151, 189, 221, 310, 351, 501, 24956, 60679,
    65, 35087, 182, 201, 270, 339, 452, 16747, 63583, 8, 130, 127, 16580, 41167, 16660, 50191, 389, 25035,
    60424, 56, 114, 111, 212, 272, 298, 432, 438, 16876, 64143, 51, 144, 109, 226, 207, 312, 384,
    390, 16828, 57487, 32, 36111, 40971, 219, 306, 344, 357, 16811, 53375, 82, 62, 122, 16593, 43055, 45407,
    418, 456, 510, 59599, 88, 146, 143, 228, 44289, 275, 319, 402, 440, 16878, 56511, 16457, 33794, 147,
    163, 246, 264, 327, 387, 425, 447, 68, 14, 136, 190, 16621, 47375, 466, 16888, 55855, 33, 27,
    102, 172, 44159, 291, 345, 373, 16827, 55423, 4, 37127, 133, 171, 251, 292, 346, 405, 16859, 59775,
    90, 117, 169, 234, 304, 338, 436, 16890, 64607, 3, 60, 104, 16559, 39343, 267, 330, 435, 489,
    511};
void build_schedule(Params& prm, int pairs) {
  for (int i = 0; i < kAttnUnits; i++) prm.blk[i] = (uint16_t)(i | 1 << 12);
  uint8_t delay[kMaxPairs] = {};
  static uint16_t lists[kMaxPairs][kMaxUnits];
  int n[kMaxPairs] = {};
  double t[kMaxPairs] = {};
  const double ta = 40.0, to = 59.0;
  for (int u = 0; u < kUnits; u++) {
    int p = 0;
    for (int q = 1; q < pairs; q++)
      if (t[q] < t[p] - 1e-9) p = q;
    uint16_t code;
    if (u < kAttnUnits) {
      code = (uint16_t)u;
    } else {
      const int o = u - kAttnUnits, g2 = o / 5, r = o % 5;
      code = (uint16_t)(0x800F | (r < 4 ? ((2 * g2 + (r >> 1)) << 2) | (r & 1) : ((2 * g2) << 2) | 2) << 8);
    }
    lists[p][n[p]++] = code;
    t[p] += u < kAttnUnits ? ta : to;
  }
  if (pairs == kTunedPairs) {
    for (int p = 0, o = 0; p < pairs; p++) {
      n[p] = kTunedLen[p];
      delay[p] = kTunedDelay[p];
      for (int i = 0; i < n[p]; i++) lists[p][i] = kTunedUnit[o++];
    }
    for (int i = 0; i < kAttnUnits; i++) prm.blk[i] = kTunedBlock[i];
  }
  int o = 0;
  for (int p = 0; p < pairs; p++) {
    prm.head[p] = o | n[p] << 10 | delay[p] << 15 | (uint32_t)(lists[p][0] & 511) << 23;
    for (int i = 0; i < n[p]; i++) prm.unit[o++] = lists[p][i];
  }
}

}

extern "C" void kernel_launch(void* const* d_in, const int* in_sizes, int n_in, void* d_out, int out_size) {
  (void)in_sizes; (void)n_in; (void)out_size;
  void* fnp = nullptr;
  cudaDriverEntryPointQueryResult qr;
  if (cudaGetDriverEntryPoint("cuTensorMapEncodeTiled", &fnp, cudaEnableDefault, &qr) != cudaSuccess || !fnp) return;
  EncodeFn fn = (EncodeFn)fnp;
  void* optr = nullptr;
  cudaGetSymbolAddress(&optr, g_o);
  Params prm;
  bool ok = true;
  for (int br = 0; br < 2; br++) {
    void* const* in = d_in + 5 * br;
    ok &= encode_2d(fn, &prm.x[br], in[0], (uint64_t)kB * kSq, kD, NQ);
    ok &= encode_kv(fn, &prm.kv[br], in[1]);
    ok &= encode_kv(fn, &prm.kv[2 + br], in[2]);
    ok &= encode_panels(fn, &prm.wq[br], in[3], kD, kH * kDh, 64);
    ok &= encode_panels(fn, &prm.wo[br], in[4], kH * kDh, kD, 64);
    prm.xp[br] = (const __nv_bfloat16*)in[0];
    prm.wp[br] = (const __nv_bfloat16*)in[3];
    prm.kp[br] = (const __nv_bfloat16*)in[1];
    prm.vp[br] = (const __nv_bfloat16*)in[2];
  }
  prm.op = (__nv_bfloat16*)d_out;
  ok &= encode_2d(fn, &prm.o_ld, optr, (uint64_t)kAttnUnits * 4 * kSq, 64, NQ, CU_TENSOR_MAP_SWIZZLE_NONE);
  ok &= encode_panels(fn, &prm.out, d_out, (uint64_t)kB * kSq, 2 * kD, ST_ROWS, 1);
  if (!ok) return;
  cudaFuncSetAttribute(mha_fused_kernel, cudaFuncAttributeMaxDynamicSharedMemorySize, SMEM_BYTES);
  cudaLaunchConfig_t cfg = {};
  cfg.gridDim = dim3(2);
  cfg.blockDim = dim3(384);
  cfg.dynamicSmemBytes = SMEM_BYTES;
  cfg.stream = cudaStreamPerThread;
  int pairs = 0;
  if (cudaOccupancyMaxActiveClusters(&pairs, mha_fused_kernel, &cfg) != cudaSuccess || pairs < 1) return;
  if (pairs > kMaxPairs) pairs = kMaxPairs;
  if (pairs < 24) return;
  build_schedule(prm, pairs);
  mha_fused_kernel<<<2 * pairs, 384, SMEM_BYTES, cudaStreamPerThread>>>(prm);
}
```

```cpp
#include <cuda_runtime.h>
#include <cuda_bf16.h>
#include <cuda.h>
#include <stdint.h>

namespace {

constexpr int kB = 16, kSq = 224, kD = 640, kH = 32, kSk = 1024, kDh = 128;
constexpr int kGroups = 2 * kB;
constexpr int kAttnUnits = kGroups * kH / 2;
constexpr int kOutUnits = kGroups * 5 / 2;
constexpr int kUnits = kAttnUnits + kOutUnits;
constexpr int kMaxUnits = kUnits + 64;
constexpr int kMaxPairs = 72;
constexpr int NQ = 112;
constexpr int PANEL = NQ * 128;
constexpr float kQScale = 0.08838834764831845f * 1.4426950408889634f;
constexpr int SLOT = 16384;
constexpr int NSLOT = 7;

constexpr int SM_PANEL = 0;
constexpr int SM_RING = SM_PANEL + 8 * PANEL;
constexpr int NBAR = NSLOT + 8;
constexpr int SM_RCP = SM_RING + NSLOT * SLOT;
constexpr int SM_BAR = SM_RCP + 640;
constexpr int SM_END = SM_BAR + 8 * (2 * NBAR + 12) + 32;
constexpr int SMEM_BYTES = SM_END + 1024;
static_assert(SM_RING % 1024 == 0 && PANEL % 1024 == 0, "swizzle alignment");
static_assert(SMEM_BYTES <= 232448, "smem");

struct Params {
  CUtensorMap x[2], wq[2], kv[4], wo[2];
  CUtensorMap o_ld, out;
  const __nv_bfloat16* xp[2];
  const __nv_bfloat16* wp[2];
  const __nv_bfloat16* kp[2];
  const __nv_bfloat16* vp[2];
  __nv_bfloat16* op;
  uint32_t head[kMaxPairs];
  uint16_t unit[kMaxUnits];
  uint16_t blk[kAttnUnits];
};

struct Unit {
  bool attn, mc;
  int g, hc;
  int h0, nslab;
};
__device__ __forceinline__ int unit_slabs(uint32_t u) {
  return (u & 0x8000u) ? 4 * ((u & 15) + 1 - ((u >> 4) & 15)) : kD / 64;
}
__device__ __forceinline__ Unit decode_unit(uint32_t u, uint32_t rank) {
  Unit r;
  r.attn = !(u & 0x8000u);
  r.nslab = unit_slabs(u);
  if (r.attn) {
    r.g = (u >> 4) & 31;
    r.hc = (u & 15) * 2 + rank;
    r.mc = true;
    r.h0 = 0;
  } else {
    const uint32_t t = (u >> 8) & 3;
    r.mc = t < 2;
    r.g = ((u >> 10) & 31) + (t < 2 ? 0 : rank);
    r.hc = t < 2 ? 2 * t + rank : 4;
    r.h0 = (u >> 4) & 15;
  }
  return r;
}

__device__ uint4 g_qrow[2 * kMaxPairs * 2 * 16 * 128];
__device__ unsigned int g_pc[128 * 16 * 2];
__device__ __nv_bfloat16 g_o[(size_t)kAttnUnits * kSq * 2 * kDh];
__device__ unsigned int g_ticket;
__device__ unsigned int g_rd[kAttnUnits];
__device__ unsigned int g_cnt[kAttnUnits];

constexpr int CREGS = 232, SM_OFF = -1, Q_PIN = 0x15, ST_ROWS = 56;
template <bool V>
struct BoolC {
  static constexpr bool value = V;
};
template <int V>
struct IntC {
  static constexpr int value = V;
};
template <int I, int N, class F>
__device__ __forceinline__ void static_for(F&& f) {
  if constexpr (I < N) {
    f(IntC<I>{});
    static_for<I + 1, N>(f);
  }
}
constexpr uint32_t kPat0 = 04321432100, kPat1 = 04302102100;
__host__ __device__ constexpr int x_pos(int pat, int k) { return ((pat == 0 ? kPat0 : kPat1) >> 3 * k) & 7; }
__host__ __device__ constexpr int x_off(int pat, int k) { return k == 0 ? 0 : x_off(pat, k - 1) + (x_pos(pat, k - 1) == 0 ? 3 : 1); }
__host__ __device__ constexpr int w_cut(int i) { return 56 * i / 5; }
__device__ __forceinline__ uint32_t unit_pattern(uint32_t u, uint32_t prev) {
  return (prev & 0x8000u) && unit_slabs(u) >= 10 ? kPat1 : kPat0;
}
__device__ __forceinline__ uint32_t next_pos(uint32_t pos, int k, uint32_t pat) {
  return k < 9 ? (pat >> (3 * k + 3)) & 7 : (pos & 3) + 1;
}
__device__ __forceinline__ uint32_t pick(bool c, uint32_t a, uint32_t b) {
  uint32_t r;
  asm("{\n.reg .pred p;\nsetp.ne.u32 p, %1, 0;\nselp.u32 %0, %2, %3, p;\n}" : "=r"(r) : "r"((uint32_t)c), "r"(a), "r"(b));
  return r;
}
__device__ __forceinline__ uint32_t ring_round(uint32_t i) { return (i * 9363u) >> 16; }
__device__ __forceinline__ uint32_t ring_slot(uint32_t i) { return i - NSLOT * ring_round(i); }
__device__ __forceinline__ uint32_t ring_par(uint32_t i) { return ring_round(i) & 1; }

__device__ __forceinline__ uint32_t smem_u32(const void* p) { return (uint32_t)__cvta_generic_to_shared(p); }
__device__ __forceinline__ void mbar_init(uint32_t bar, uint32_t cnt) {
  asm volatile("mbarrier.init.shared::cta.b64 [%0], %1;" ::"r"(bar), "r"(cnt));
}
__device__ __forceinline__ void mbar_arrive1_if(uint32_t bar, bool pred) {
  asm volatile("{\n.reg .pred p;\nsetp.ne.u32 p, %1, 0;\n@p mbarrier.arrive.shared::cta.b64 _, [%0];\n}" ::"r"(bar), "r"((uint32_t)pred)
               : "memory");
}
__device__ __forceinline__ void mbar_wait_warp(uint32_t bar, uint32_t parity) {
  asm volatile(
      "{\n.reg .pred p, q;\n.reg .u32 c;\n"
      "mov.u32 c, 0;\n"
      "SPIN:\n"
      "mbarrier.try_wait.parity.shared::cta.b64 p, [%0], %1;\n"
      "vote.sync.all.pred q, p, 0xffffffff;\n"
      "@q bra.uni DONE;\n"
      "add.u32 c, c, 1;\n"
      "setp.gt.u32 q, c, 0x1000000;\n"
      "@q trap;\n"
      "bra.uni SPIN;\n"
      "DONE:\n}" ::"r"(bar),
      "r"(parity)
      : "memory");
}
__device__ __forceinline__ uint32_t mbar_test(uint32_t bar, uint32_t parity) {
  uint32_t ok;
  asm volatile(
      "{\n.reg .pred p;\nmbarrier.test_wait.parity.shared::cta.b64 p, [%1], %2;\nselp.u32 %0, 1, 0, p;\n}"
      : "=r"(ok)
      : "r"(bar), "r"(parity)
      : "memory");
  return ok;
}
__device__ __forceinline__ uint32_t mbar_test_if(uint32_t bar, uint32_t parity, bool pred) {
  uint32_t ok;
  asm volatile(
      "{\n.reg .pred p, q;\nsetp.ne.u32 q, %3, 0;\nsetp.eq.u32 p, %3, 0;\n"
      "@q mbarrier.test_wait.parity.shared::cta.b64 p, [%1], %2;\nselp.u32 %0, 1, 0, p;\n}"
      : "=r"(ok)
      : "r"(bar), "r"(parity), "r"((uint32_t)pred)
      : "memory");
  return ok;
}
#define ELECTED "{\n.reg .pred e;\nelect.sync _|e, 0xffffffff;\n@e "
constexpr uint64_t kEvictFirst = 0x12F0000000000000ull, kEvictNormal = 0x1000000000000000ull;
__device__ __forceinline__ void flag_wait(const unsigned int* p, uint32_t target) {
  asm volatile(
      "{\n.reg .pred p, q;\n.reg .u32 c, v;\n"
      "mov.u32 c, 0;\n"
      "SPIN:\n"
      "ld.acquire.gpu.global.u32 v, [%0];\n"
      "setp.ge.u32 p, v, %1;\n"
      "vote.sync.all.pred q, p, 0xffffffff;\n"
      "@q bra.uni DONE;\n"
      "nanosleep.u32 200;\n"
      "add.u32 c, c, 1;\n"
      "setp.gt.u32 q, c, 0x1000000;\n"
      "@q trap;\n"
      "bra.uni SPIN;\n"
      "DONE:\n}" ::"l"(p),
      "r"(target)
      : "memory");
}
__device__ __forceinline__ uint32_t flags_wait(const unsigned int* p, uint32_t target, uint32_t need) {
  uint32_t m;
  asm volatile(
      "{\n.reg .pred p, q;\n.reg .u32 c, v;\n"
      "mov.u32 c, 0;\n"
      "SPIN:\n"
      "ld.acquire.gpu.global.u32 v, [%1];\n"
      "setp.ge.u32 p, v, %2;\n"
      "vote.sync.ballot.b32 %0, p, 0xffffffff;\n"
      "and.b32 v, %0, %3;\n"
      "setp.eq.u32 q, v, %3;\n"
      "@q bra.uni DONE;\n"
      "add.u32 c, c, 1;\n"
      "setp.gt.u32 q, c, 0x1000000;\n"
      "@q trap;\n"
      "bra.uni SPIN;\n"
      "DONE:\n"
      "fence.proxy.async.global;\n}"
      : "=&r"(m)
      : "l"(p), "r"(target), "r"(need)
      : "memory");
  return m;
}
__device__ __forceinline__ void e_arrive(uint32_t bar, uint32_t n) {
  asm volatile(ELECTED "mbarrier.arrive.shared::cta.b64 _, [%0], %1;\n}" ::"r"(bar), "r"(n) : "memory");
}
__device__ __forceinline__ void e_expect_tx(uint32_t bar, uint32_t bytes) {
  asm volatile(ELECTED "mbarrier.arrive.expect_tx.shared::cta.b64 _, [%0], %1;\n}" ::"r"(bar), "r"(bytes) : "memory");
}
__device__ __forceinline__ void tma_ld2(uint32_t dst, const CUtensorMap* m, int c0, int c1, uint32_t bar, uint64_t pol) {
  asm volatile(ELECTED
               "cp.async.bulk.tensor.2d.shared::cluster.global.mbarrier::complete_tx::bytes.L2::cache_hint [%0], [%1, {%3, %4}], "
               "[%2], %5;\n}" ::"r"(dst),
               "l"(m), "r"(bar), "r"(c0), "r"(c1), "l"(pol)
               : "memory");
}
__device__ __forceinline__ void tma_ld2_mc(uint32_t dst, const CUtensorMap* m, int c0, int c1, uint32_t bar, uint64_t pol) {
  asm volatile(ELECTED
               "cp.async.bulk.tensor.2d.shared::cluster.global.mbarrier::complete_tx::bytes.multicast::cluster.L2::cache_hint "
               "[%0], [%1, {%3, %4}], [%2], %5, %6;\n}" ::"r"(dst),
               "l"(m), "r"(bar), "r"(c0), "r"(c1), "h"((uint16_t)3), "l"(pol)
               : "memory");
}
__device__ __forceinline__ void tma_ld3(uint32_t dst, const CUtensorMap* m, int c1, int c2, uint32_t bar, uint64_t pol) {
  asm volatile(ELECTED
               "cp.async.bulk.tensor.3d.shared::cluster.global.mbarrier::complete_tx::bytes.L2::cache_hint [%0], [%1, {%3, %4, "
               "%5}], [%2], %6;\n}" ::"r"(dst),
               "l"(m), "r"(bar), "r"(0), "r"(c1), "r"(c2), "l"(pol)
               : "memory");
}
__device__ __forceinline__ void tma_ld4(uint32_t dst, const CUtensorMap* m, int c3, uint32_t bar, uint64_t pol) {
  asm volatile(ELECTED
               "cp.async.bulk.tensor.4d.shared::cluster.global.mbarrier::complete_tx::bytes.L2::cache_hint [%0], [%1, {%3, %3, "
               "%3, %4}], [%2], %5;\n}" ::"r"(dst),
               "l"(m), "r"(bar), "r"(0), "r"(c3), "l"(pol)
               : "memory");
}
__device__ __forceinline__ void tma_st3(const CUtensorMap* m, int c1, int c2, uint32_t src, bool add) {
  if (add)
    asm volatile(ELECTED "cp.reduce.async.bulk.tensor.3d.global.shared::cta.add.bulk_group [%0, {%2, %3, %4}], [%1];\n}" ::"l"(m), "r"(src),
                 "r"(0), "r"(c1), "r"(c2)
                 : "memory");
  else
    asm volatile(ELECTED "cp.async.bulk.tensor.3d.global.shared::cta.bulk_group [%0, {%2, %3, %4}], [%1];\n}" ::"l"(m), "r"(src), "r"(0),
                 "r"(c1), "r"(c2)
                 : "memory");
}
__device__ __forceinline__ void wgmma_fence() { asm volatile("wgmma.fence.sync.aligned;" ::: "memory"); }
__device__ __forceinline__ void wgmma_commit() { asm volatile("wgmma.commit_group.sync.aligned;" ::: "memory"); }
template <int N>
__device__ __forceinline__ void wgmma_wait() {
  asm volatile("wgmma.wait_group.sync.aligned %0;" ::"n"(N) : "memory");
}
template <int N>
__device__ __forceinline__ void wgmma_wait_pin(int never, int c) {
  asm volatile("{\n.reg .pred p;\nsetp.eq.u32 p, %1, %2;\nAGAIN:\nwgmma.wait_group.sync.aligned %0;\n@p bra.uni AGAIN;\n}" ::"n"(N),
               "r"(never), "r"(c)
               : "memory");
}
__device__ __forceinline__ void pin_order(int never, int c) {
  asm volatile("{\n.reg .pred p;\nsetp.eq.u32 p, %0, %1;\nAGAIN:\n@p nanosleep.u32 1;\n@p bra.uni AGAIN;\n}" ::"r"(never), "r"(c) : "memory");
}
template <int N>
__device__ __forceinline__ void fence_regs(float (&d)[N]) {
#pragma unroll
  for (int i = 0; i < N; i++) asm volatile("" : "+f"(d[i])::"memory");
}
__device__ __forceinline__ void fence_async_smem() { asm volatile("fence.proxy.async.shared::cta;" ::: "memory"); }
__device__ __forceinline__ void bar_sync(int id, int n) { asm volatile("bar.sync %0, %1;" ::"r"(id), "r"(n) : "memory"); }
__device__ __forceinline__ void bar_arrive(int id, int n) {
  asm volatile("bar.arrive %0, %1;" ::"r"(id), "r"(n) : "memory");
}
__device__ __forceinline__ void stsm_x4_t(uint32_t addr, uint32_t r0, uint32_t r1, uint32_t r2, uint32_t r3) {
  asm volatile("stmatrix.sync.aligned.m8n8.x4.trans.shared.b16 [%0], {%1, %2, %3, %4};" ::"r"(addr), "r"(r0), "r"(r1),
               "r"(r2), "r"(r3)
               : "memory");
}
__device__ __forceinline__ void stsm_x4_t_pin(uint32_t addr, uint32_t r0, uint32_t r1, uint32_t r2, uint32_t r3, int never, int c) {
  asm volatile(
      "{\n.reg .pred p;\nsetp.eq.u32 p, %5, %6;\nAGAIN:\n"
      "stmatrix.sync.aligned.m8n8.x4.trans.shared.b16 [%0], {%1, %2, %3, %4};\n@p bra.uni AGAIN;\n}" ::"r"(addr),
      "r"(r0), "r"(r1), "r"(r2), "r"(r3), "r"(never), "r"(c)
      : "memory");
}
__device__ __forceinline__ void stsm_x2_t_pin(uint32_t addr, uint32_t r0, uint32_t r1, int never, int c) {
  asm volatile(
      "{\n.reg .pred p;\nsetp.eq.u32 p, %3, %4;\nAGAIN:\n"
      "stmatrix.sync.aligned.m8n8.x2.trans.shared.b16 [%0], {%1, %2};\n@p bra.uni AGAIN;\n}" ::"r"(addr),
      "r"(r0), "r"(r1), "r"(never), "r"(c)
      : "memory");
}
__device__ __forceinline__ uint32_t pack_bf16(float lo, float hi) {
  uint32_t r;
  asm("cvt.rn.bf16x2.f32 %0, %1, %2;" : "=r"(r) : "f"(hi), "f"(lo));
  return r;
}
__device__ __forceinline__ float ex2(float x) {
  float y;
  asm("ex2.approx.ftz.f32 %0, %1;" : "=f"(y) : "f"(x));
  return y;
}
__device__ __forceinline__ uint32_t mk_desc(uint32_t addr) { return (1u << 16) | ((addr & 0x3FFFFu) >> 4); }

template <int TA, int TB = 0, int KV = 0>
__device__ __forceinline__ void wgmma_n112(float (&d)[56], uint32_t descA, uint32_t descB, int scaleD) {
  asm volatile(
      "{\n.reg .pred p;\n.reg .b32 hi, hb;\n.reg .b64 da, db;\nsetp.ne.b32 p, %58, 0;\n"
      "mov.b32 hi, %62;\nmov.b32 hb, %61;\nmov.b64 da, {%56, hi};\nmov.b64 db, {%57, hb};\n"
      "wgmma.mma_async.sync.aligned.m64n112k16.f32.bf16.bf16 "
      "{%0, %1, %2, %3, %4, %5, %6, %7, %8, %9, %10, %11, %12, %13, "
      "%14, %15, %16, %17, %18, %19, %20, %21, %22, %23, %24, %25, %26, %27, "
      "%28, %29, %30, %31, %32, %33, %34, %35, %36, %37, %38, %39, %40, %41, "
      "%42, %43, %44, %45, %46, %47, %48, %49, %50, %51, %52, %53, %54, %55}, "
      "da, db, p, 1, 1, %59, %60;\n}\n"
      : "+f"(d[0]), "+f"(d[1]), "+f"(d[2]), "+f"(d[3]), "+f"(d[4]), "+f"(d[5]), "+f"(d[6]),
        "+f"(d[7]), "+f"(d[8]), "+f"(d[9]), "+f"(d[10]), "+f"(d[11]), "+f"(d[12]), "+f"(d[13]),
        "+f"(d[14]), "+f"(d[15]), "+f"(d[16]), "+f"(d[17]), "+f"(d[18]), "+f"(d[19]), "+f"(d[20]),
        "+f"(d[21]), "+f"(d[22]), "+f"(d[23]), "+f"(d[24]), "+f"(d[25]), "+f"(d[26]), "+f"(d[27]),
        "+f"(d[28]), "+f"(d[29]), "+f"(d[30]), "+f"(d[31]), "+f"(d[32]), "+f"(d[33]), "+f"(d[34]),
        "+f"(d[35]), "+f"(d[36]), "+f"(d[37]), "+f"(d[38]), "+f"(d[39]), "+f"(d[40]), "+f"(d[41]),
        "+f"(d[42]), "+f"(d[43]), "+f"(d[44]), "+f"(d[45]), "+f"(d[46]), "+f"(d[47]), "+f"(d[48]),
        "+f"(d[49]), "+f"(d[50]), "+f"(d[51]), "+f"(d[52]), "+f"(d[53]), "+f"(d[54]), "+f"(d[55])
      : "r"(descA), "r"(descB), "r"(scaleD), "n"(TA), "n"(TB), "n"(TB ? 8 : 0x40000040), "n"(KV ? 0x40000080 : 0x40000040));
}

template <int T>
__device__ __forceinline__ void pack_half(float (&pk)[56], const float (&a)[56]) {
#pragma unroll
  for (int i = 0; i < 28; i++) pk[28 * T + i] = __uint_as_float(pack_bf16(a[2 * i], a[2 * i + 1]));
}
template <int T>
__device__ __forceinline__ void fence_half(float (&pk)[56]) {
#pragma unroll
  for (int i = 0; i < 28; i++) asm volatile("" : "+f"(pk[28 * T + i])::"memory");
}
template <int T, int LO = 0, int HI = 7>
__device__ __forceinline__ void store_half(uint32_t addr, const float (&pk)[56]) {
#pragma unroll
  for (int q = LO; q < HI; q++) {
    const float* r = pk + 28 * T + 4 * q;
    stsm_x4_t(addr + T * PANEL + q * 2048, __float_as_uint(r[0]), __float_as_uint(r[1]), __float_as_uint(r[2]), __float_as_uint(r[3]));
  }
}

template <int T>
__device__ __forceinline__ void q_half(uint32_t addr, float (&pk)[56], const float (&a)[56], int never) {
#pragma unroll
  for (int q = 0; q < 7; q++) {
    uint32_t r[4];
#pragma unroll
    for (int i = 0; i < 4; i++) {
      r[i] = pack_bf16(a[8 * q + 2 * i] * kQScale, a[8 * q + 2 * i + 1] * kQScale);
      pk[28 * T + 4 * q + i] = __uint_as_float(r[i]);
    }
    if (q < 6 && (Q_PIN >> q & 1)) stsm_x4_t_pin(addr + T * PANEL + q * 2048, r[0], r[1], r[2], r[3], never, 32 + 2 * (7 * T + q));
    else stsm_x4_t(addr + T * PANEL + q * 2048, r[0], r[1], r[2], r[3]);
  }
}

__device__ __forceinline__ float bf_lo(uint32_t u) { return __uint_as_float(u << 16); }
__device__ __forceinline__ float bf_hi(uint32_t u) { return __uint_as_float(u & 0xFFFF0000u); }

__device__ __forceinline__ void fma8(float* o, float a, const uint4& w, float c) {
  o[0] = fmaf(a, bf_lo(w.x), o[0] * c), o[1] = fmaf(a, bf_hi(w.x), o[1] * c);
  o[2] = fmaf(a, bf_lo(w.y), o[2] * c), o[3] = fmaf(a, bf_hi(w.y), o[3] * c);
  o[4] = fmaf(a, bf_lo(w.z), o[4] * c), o[5] = fmaf(a, bf_hi(w.z), o[5] * c);
  o[6] = fmaf(a, bf_lo(w.w), o[6] * c), o[7] = fmaf(a, bf_hi(w.w), o[7] * c);
}
__device__ __forceinline__ void slow_rows(uint4* qrow, int tq, const __nv_bfloat16* xp, const __nv_bfloat16* wp,
                                          const __nv_bfloat16* kp, const __nv_bfloat16* vp, __nv_bfloat16* op) {
  if (tq >= NQ) return;
#pragma unroll 1
  for (int c = 0; c < 16; c++) {
    float q[8] = {};
#pragma unroll 1
    for (int k = 0; k < kD; k++)
      fma8(q, __bfloat162float(xp[tq * kD + k]), __ldg(reinterpret_cast<const uint4*>(wp + k * (kH * kDh)) + c), 1.f);
    qrow[c * 128] = make_uint4(pack_bf16(q[0] * kQScale, q[1] * kQScale), pack_bf16(q[2] * kQScale, q[3] * kQScale),
                               pack_bf16(q[4] * kQScale, q[5] * kQScale), pack_bf16(q[6] * kQScale, q[7] * kQScale));
  }
#pragma unroll 1
  for (int pass = 0; pass < 4; pass++) {
    float o[32] = {}, m = -INFINITY, l = 0.f;
#pragma unroll 1
    for (int key = 0; key < kSk; key++) {
      const uint4* kr = reinterpret_cast<const uint4*>(kp + key * kDh);
      const uint4* vr = reinterpret_cast<const uint4*>(vp + key * kDh) + 4 * pass;
      float s = 0.f;
#pragma unroll 1
      for (int c = 0; c < 16; c++) {
        const uint4 q = qrow[c * 128], k = __ldg(kr + c);
        s = fmaf(bf_lo(q.x), bf_lo(k.x), s); s = fmaf(bf_hi(q.x), bf_hi(k.x), s);
        s = fmaf(bf_lo(q.y), bf_lo(k.y), s); s = fmaf(bf_hi(q.y), bf_hi(k.y), s);
        s = fmaf(bf_lo(q.z), bf_lo(k.z), s); s = fmaf(bf_hi(q.z), bf_hi(k.z), s);
        s = fmaf(bf_lo(q.w), bf_lo(k.w), s); s = fmaf(bf_hi(q.w), bf_hi(k.w), s);
      }
      const float mn = fmaxf(m, s);
      const float ms = (mn == -INFINITY) ? 0.f : mn;
      const float corr = ex2(m - ms), p = ex2(s - ms);
      l = l * corr + p;
      m = mn;
      const float pb = __bfloat162float(__float2bfloat16(p));
#pragma unroll
      for (int c = 0; c < 4; c++) fma8(o + 8 * c, pb, __ldg(vr + c), corr);
    }
    const float sc = __fdividef(1.f, l);
    __nv_bfloat16* dst = op + (pass >> 1) * PANEL + (pass & 1) * 3584 + (tq >> 3) * 64 + (tq & 7);
#pragma unroll
    for (int d = 0; d < 32; d++) dst[(d >> 3) * 896 + (d & 7) * 8] = __float2bfloat16(o[d] * sc);
  }
}

__device__ __forceinline__ uint32_t launch_epoch() { return atomicAdd(&g_ticket, 1u) / gridDim.x; }

__global__ void __cluster_dims__(2, 1, 1) __launch_bounds__(384, 1) mha_fused_kernel(const __grid_constant__ Params prm) {
  extern __shared__ __align__(1024) unsigned char smem_raw[];

  const uint32_t sb = (smem_u32(smem_raw) + 1023u) & ~1023u;
  const uint32_t full0 = sb + SM_BAR, empty0 = full0 + 8 * NBAR, sfull0 = empty0 + 8 * NBAR;
  const uint32_t cred0 = sfull0 + 32, redo0 = cred0 + 64, epoch_addr = redo0 + 8, go_bar = redo0 + 16, ok_bar = redo0 + 24;
  const uint32_t rank = blockIdx.x & 1, pair = blockIdx.x >> 1;
  const uint32_t head = prm.head[pair];
  const int u_begin = head & 1023, u_end = u_begin + ((head >> 10) & 31);
  const uint32_t delay = ((head >> 15) & 255) * 256;
  const int tid = threadIdx.x;
  const int wid = __shfl_sync(0xffffffffu, tid >> 5, 0), wg = wid >> 2;

  if (wg == 2) {
    asm volatile("setmaxnreg.dec.sync.aligned.u32 %0;" ::"n"(504 - 2 * CREGS));
    const int warp = wid & 3, lane = tid & 31;
    bar_sync(0, 384);
    asm volatile("barrier.cluster.arrive.relaxed.aligned;" ::: "memory");
    if (warp < 3 && delay)
      asm volatile(
          "{\n.reg .pred p, q;\n.reg .u32 t0, t;\nmov.u32 t0, %%clock;\n"
          "SPIN:\nnanosleep.u32 100;\nmov.u32 t, %%clock;\nsub.u32 t, t, t0;\nsetp.lt.u32 p, t, %0;\n"
          "vote.sync.all.pred q, p, 0xffffffff;\n@q bra.uni SPIN;\n}" ::"r"(delay));
    auto slot_addr = [&](uint32_t i) { return sb + SM_RING + ring_slot(i) * SLOT; };
    auto full_bar = [&](uint32_t i) { return full0 + 8 * ring_slot(i); };
    const int count = (head >> 10) & 31;
    if (warp == 0) {
      uint32_t it = 6, prev = 0, code = head >> 23;
      auto acquire = [&](uint32_t i) { mbar_wait_warp(empty0 + 8 * ring_slot(i), ring_par(i) ^ 1); };
      uint32_t rblk = 0, rleft = 0;
      auto block_read = [&]() {
        asm volatile(ELECTED "red.relaxed.gpu.global.add.u32 [%0], 1;\n}" ::"l"(&g_rd[prm.blk[rblk] & 511]) : "memory");
        rblk++;
        rleft--;
      };
#pragma unroll 1
      for (int n = 1; n <= count; n++) {
        const uint32_t pat = unit_pattern(code, prev);
        const Unit u = decode_unit(code, rank);
        const int br = u.g >> 4;
        const CUtensorMap* mw = (u.attn ? prm.wq : prm.wo) + br;
        const int nslab = u.nslab;
#pragma unroll 1
        for (int k = n == 1 ? 2 : 0, pos = n == 1; k < nslab; k++) {
          const uint32_t i = it + (pos == 0);
          acquire(i);
          e_expect_tx(full_bar(i), SLOT);
          tma_ld3(slot_addr(i), mw, u.h0 * 256 + k * 64, u.hc * 2, full_bar(i), kEvictNormal);
          if (rleft && (k & 3) == 2 && k != 6) {
#pragma unroll 1
            do block_read();
            while (rleft && k == 2);
          }
          if (!u.attn && k == 4) rblk = u.g * 16 + u.h0, rleft = nslab >> 2;
          it = i + 1 + (pos == 0);
          pos = next_pos(pos, k, pat);
        }
        if (u.attn) {
          const int row0 = ((u.g & 15) * kH + u.hc) * kSk;
#pragma unroll 1
          for (int j = 0; j < kSk / 32; j++, it++) {
            acquire(it);
            e_expect_tx(full_bar(it), SLOT);
            const int isv = j == 31 || (j > 0 && !(j & 1));
            tma_ld4(slot_addr(it), &prm.kv[2 * isv + br], row0 / 8 + (((j + 1) >> 1) - isv) * 8, full_bar(it), kEvictFirst);
            if (j == kSk / 32 - 2) e_arrive(go_bar, 1);
          }
        }
        prev = code;
        code = prm.unit[u_begin + n];
      }
      if (rleft) {
        acquire(it + NSLOT - 1);
#pragma unroll 1
        while (rleft) block_read();
      }
    } else if (warp < 3) {
      asm volatile("barrier.cluster.wait.acquire.aligned;" ::: "memory");
      const int w = warp == 1 ? rank : rank ^ 1;
      uint32_t it = 6, nc = 0, pph = 0, go_ph = 0, prev = 0, code = head >> 23;
      const unsigned int* flags0 = g_cnt + (lane & 15);
      uint32_t peer_cred0;
      asm("mapa.shared::cluster.u32 %0, %1, %2;" : "=r"(peer_cred0) : "r"(cred0), "r"(rank ^ 1));
#pragma unroll 1
      for (int n = 1; n <= count; n++) {
        const uint32_t pat = unit_pattern(code, prev);
        Unit u = decode_unit(code, rank);
        const CUtensorMap* mx = u.attn ? &prm.x[u.g >> 4] : &prm.o_ld;
        const int nslab = u.nslab;
        const bool polls = !u.attn && (warp == 1 || !u.mc);
        uint32_t done = 0, ready = 0;
        if (polls) {
          asm volatile("ld.volatile.shared.u32 %0, [%1];" : "=r"(done) : "r"(epoch_addr) : "memory");
          done *= 2;
        }
        const unsigned int* flags;
        asm("add.u64 %0, %1, %2;" : "=l"(flags) : "l"(flags0), "l"((uint64_t)(uint32_t)(u.g * 64)));
        const uint64_t xpol = u.attn ? kEvictNormal : kEvictFirst;
        int xcol = n == 1 ? 128 : 0, xrow = (u.g & 15) * kSq + w * NQ;
#pragma unroll 1
        for (int k = n == 1 ? 2 : 0, pos = n == 1; k < nslab; k++) {
          if (polls && (k & 2) == 0) {
            const uint32_t hp = u.h0 + (k >> 2);
            if ((k & 1) == 0) {
              if (!(ready >> hp & 1)) ready = flags_wait(flags, done, 1u << hp);
              xrow = (prm.blk[u.g * 16 + hp] & 511) * (4 * kSq) + w * NQ;
            } else if (!(ready >> hp & 2)) {
              ready = flags_wait(flags, done, 0);
            }
          }
          const uint32_t i = it + 2 * w, q = pos - 1;
          const uint32_t fbar = full0 + 8 * (pos == 0 ? ring_slot(i) : NSLOT + 4 * w + q);
          const uint32_t dst = pos == 0 ? slot_addr(i) : sb + SM_PANEL + (4 * w + q) * PANEL;
          const uint32_t par = (pos == 0 ? ring_round(i) : pph >> q) & 1;
          pph ^= pos == 0 ? 0u : 1u << q;
          it += 1 + 2 * (pos == 0);
          pos = next_pos(pos, k, pat);
          mbar_wait_warp(fbar + 8 * NBAR, par ^ 1);
          e_expect_tx(fbar, PANEL);
          if (!u.mc) {
            tma_ld2(dst, mx, xcol, xrow, fbar, xpol);
          } else {
            if (warp == 1) {
              if (it > 10) mbar_wait_warp(cred0 + 8 * (nc & 7), (nc >> 3) & 1);
              tma_ld2_mc(dst, mx, xcol, xrow, fbar, xpol);
            } else if (it > 10) {
              asm volatile(ELECTED "mbarrier.arrive.shared::cluster.b64 _, [%0];\n}" ::"r"(peer_cred0 + 8 * (nc & 7)) : "memory");
            }
            nc += it > 10;
          }
          xcol += u.attn ? 64 : 0;
          xrow += u.attn ? 0 : kSq;
        }
        if (u.attn) {
          mbar_wait_warp(go_bar, go_ph);
          go_ph ^= 1;
          it += kSk / 32;
        }
        prev = code;
        code = prm.unit[u_begin + n];
      }
    } else {
      uint32_t epoch = 0, prev = 0;
      if (lane == 0) epoch = launch_epoch();
      epoch = __shfl_sync(0xffffffffu, epoch, 0);
      asm volatile("st.volatile.shared.u32 [%0], %1;" ::"r"(epoch_addr), "r"(epoch + 1) : "memory");
      auto publish = [&](unsigned int* p) {
        __syncwarp();
        asm volatile(ELECTED "red.release.gpu.global.add.u32 [%0], 1;\n}" ::"l"(p) : "memory");
      };
#pragma unroll 1
      for (int n = 0; n < count; n++) {
        const uint32_t code = prm.unit[u_begin + n], ph = n & 1;
        if (!(code & 0x8000u)) {
          const uint32_t blk = prm.blk[code & 511], gen = (blk >> 9) & 7;
          if (gen > 0) flag_wait(&g_rd[blk & 511], 5 * (epoch * (blk >> 12) + gen));
        }
        __syncwarp();
        e_arrive(ok_bar, 1);
        const bool clear = (code & 0xA000u) == 0x2000u;
        const uint32_t oc = clear ? prm.unit[u_begin + n + 1] : code;
        const Unit u = decode_unit(oc, rank);
        const int row = (u.g & 15) * kSq, cb = (u.g >> 4) * 10 + u.hc * 2;
        unsigned int* pc = g_pc + (oc >> 8 & 127) * 32 + rank;
        if (!(code & 0x8000u)) {
          if (clear) {
            uint4* o = reinterpret_cast<uint4*>(prm.op + (row + (lane >> 4)) * (2 * kD) + cb * 64) + (lane & 15);
#pragma unroll 1
            for (int r = 0; r < kSq / 2; r++, o += 4 * kD / 8) {
              *o = make_uint4(0, 0, 0, 0);
              __nanosleep(40);
            }
            publish(pc + 2 * (oc & 15));
          }
#pragma unroll 1
          for (int q = 0; q < 4; q++) mbar_wait_warp(sfull0 + 8 * q, ph);
          publish(&g_cnt[code & 511]);
        } else {
          const bool cleared = (prev & 0xA000u) == 0x2000u;
          if (u.h0) flag_wait(pc + 2 * (u.h0 - 1), epoch + 1);
          asm volatile("fence.proxy.async.global;" ::: "memory");
#pragma unroll 1
          for (int q = 0; q < 4; q++) {
            const int w = n + 1 < count ? q & 1 : q >> 1, t = n + 1 < count ? q >> 1 : q & 1;
            mbar_wait_warp(sfull0 + 8 * (2 * t + w), ph);
            fence_async_smem();
#pragma unroll 1
            for (int r = 0; r < NQ; r += ST_ROWS) {
              tma_st3(&prm.out, row + w * NQ + r, cb + t, sb + SM_PANEL + (4 * w + 2 + t) * PANEL + r * 128, u.h0 || cleared);
              asm volatile("cp.async.bulk.commit_group;" ::: "memory");
              if (n + 1 < count) asm volatile("cp.async.bulk.wait_group.read 0;" ::: "memory");
            }
            __syncwarp();
            e_arrive(empty0 + 8 * (NSLOT + 4 * w + 2 + t), 2);
          }
          if ((code & 15) != 15 && !cleared) {
            asm volatile("cp.async.bulk.wait_group 0;" ::: "memory");
            asm volatile("fence.proxy.async.global;" ::: "memory");
            publish(pc + 2 * (code & 15));
          }
        }
        prev = code;
      }
      asm volatile("cp.async.bulk.wait_group 0;" ::: "memory");
    }
  } else {
    const int tq = tid & 127, lane = tid & 31, warp = tq >> 5;
    if (tid == 0) {
#pragma unroll
      for (int i = 0; i < NBAR; i++) {
        mbar_init(full0 + 8 * i, 1);
        mbar_init(empty0 + 8 * i, 2);
      }
#pragma unroll
      for (int i = 0; i < 12; i++) mbar_init(sfull0 + 8 * i, i < 4 ? 4 : 1);
      mbar_init(go_bar, 1);
      mbar_init(ok_bar, 1);
      asm volatile("st.shared.v4.u32 [%0], {%1, %1, %1, %1};" ::"r"(redo0), "r"(0) : "memory");
      asm volatile("fence.mbarrier_init.release.cluster;" ::: "memory");
      fence_async_smem();
    }
    if (wid == 0) {
      __syncwarp();
      const Unit u = decode_unit(head >> 23, rank);
#pragma unroll
      for (int i = 0; i < 6; i++) {
        e_expect_tx(full0 + 8 * i, i % 3 == 1 ? SLOT : PANEL);
        if (i % 3 == 1) tma_ld3(sb + SM_RING + i * SLOT, &prm.wq[u.g >> 4], i / 3 * 64, u.hc * 2, full0 + 8 * i, kEvictNormal);
        else tma_ld2(sb + SM_RING + i * SLOT, &prm.x[u.g >> 4], i / 3 * 64, (u.g & 15) * kSq + i % 3 / 2 * NQ, full0 + 8 * i, kEvictNormal);
      }
    } else if (wid < 5) {
      asm volatile(ELECTED "prefetch.tensormap [%0];\n}" ::"l"(prm.x + 2 * (wid - 1) + (head >> 31)) : "memory");
    }
    bar_sync(0, 384);
    asm volatile("barrier.cluster.arrive.relaxed.aligned;" ::: "memory");
    asm volatile("setmaxnreg.inc.sync.aligned.u32 %0;" ::"n"(CREGS));
    const uint32_t stage = sb + SM_PANEL + wg * 4 * PANEL;
    const uint32_t st_q = __shfl_sync(
        0xffffffffu, stage + ((lane >> 4) * 8 + (lane & 7)) * 128 + (((2 * warp + ((lane >> 3) & 1)) ^ (lane & 7)) << 4), lane);
    const uint32_t st_p = st_q + 2 * PANEL;
    const uint32_t dq = mk_desc(stage), dring = mk_desc(sb + SM_RING);
    float acc[2][56], s[56] = {};
    const int never = (sb >> 24) & ~1u;
    uint32_t it = 0, pph = 0;
    auto wait_full = [&](uint32_t i) { mbar_wait_warp(full0 + 8 * ring_slot(i), ring_par(i)); };
    auto test = [&](uint32_t bar, uint32_t par) { return mbar_test_if(bar, par, warp == 0); };
    auto probe = [&](uint32_t i) { return test(full0 + 8 * ring_slot(i), ring_par(i)); };
    auto release = [&](uint32_t i) { mbar_arrive1_if(empty0 + 8 * ring_slot(i), tq == 0); };
    auto slot_desc = [&](uint32_t i) { return dring + ring_slot(i) * (SLOT >> 4); };
    if (wg == 1) bar_arrive(1, 256);

    struct Fin {
      uint32_t rp[16];
      char* dst;
    };
    uint32_t ps[14] = {};
    float l[28] = {};
    auto step_sums = [&]() {
#pragma unroll
      for (int g = 0; g < 14; g++) asm("add.rn.bf16x2 %0, %0, %1;" : "+r"(ps[g]) : "r"(pack_bf16(l[2 * g], l[2 * g + 1])));
#pragma unroll
      for (int q = 0; q < 3; q++) stsm_x4_t(st_p + q * 2048, ps[2 * q], ps[2 * q + 7], ps[2 * q + 1], ps[2 * q + 8]);
      asm volatile("stmatrix.sync.aligned.m8n8.x2.trans.shared.b16 [%0], {%1, %2};" ::"r"(st_p + 3 * 2048), "r"(ps[6]), "r"(ps[13])
                   : "memory");
    };
    auto flag_bad = [&](bool bad) {
      asm volatile("{\n.reg .pred p;\nsetp.ne.u32 p, %1, 0;\n@p st.shared.u32 [%0], %1;\n}" ::"r"(redo0 + 4 * wg), "r"((uint32_t)bad)
                   : "memory");
    };
    auto step_finite = [&](bool live) {
      uint32_t z[4] = {0, 0, 0, 0};
#pragma unroll
      for (int i = 0; i < 28; i++)
        asm volatile("fma.rn.bf16x2 %0, %1, %2, %0;" : "+r"(z[i & 3]) : "r"(__float_as_uint(s[2 * i])), "r"(__float_as_uint(s[2 * i + 1])));
      asm volatile("add.rn.bf16x2 %0, %0, %1;" : "+r"(z[0]) : "r"(z[1]));
      asm volatile("add.rn.bf16x2 %0, %0, %1;" : "+r"(z[2]) : "r"(z[3]));
      asm volatile("add.rn.bf16x2 %0, %0, %1;" : "+r"(z[0]) : "r"(z[2]));
      flag_bad(live && (((z[0] & 0x7F807F80u) + 0x00800080u) & 0x80008000u));
    };
    auto rows_addr = [&]() {
      const uint32_t q = min(tq, NQ - 1), hi = q >= 56, n = q - 56 * hi;
      return stage + 2 * PANEL + n * 128 + ((hi ^ (n & 7)) << 4);
    };
    auto rows_load = [&](Fin& f, uint32_t a) {
#pragma unroll
      for (int c = 0; c < 4; c++)
        asm volatile("ld.shared.v4.u32 {%0, %1, %2, %3}, [%4];"
                     : "=r"(f.rp[4 * c]), "=r"(f.rp[4 * c + 1]), "=r"(f.rp[4 * c + 2]), "=r"(f.rp[4 * c + 3])
                     : "r"(a ^ (c << 5))
                     : "memory");
    };
    auto step_rows = [&](const Fin& f, bool live) {
      const uint32_t q = min(tq, NQ - 1);
      float t = 0.f, t2 = 0.f;
#pragma unroll
      for (int i = 0; i < 8; i++) {
        uint32_t v;
        asm("add.rn.bf16x2 %0, %1, %2;" : "=r"(v) : "r"(f.rp[2 * i]), "r"(f.rp[2 * i + 1]));
        t += bf_lo(v), t2 += bf_hi(v);
      }
      t += t2;
      float r;
      asm("rcp.approx.ftz.f32 %0, %1;" : "=f"(r) : "f"(t));
      asm volatile("st.shared.u16 [%0], %1;" ::"r"(sb + SM_RCP + wg * 320 + (q >> 1 & 3) * 80 + (q >> 3) * 4 + (q & 1) * 2),
                   "h"((uint16_t)pack_bf16(r, r))
                   : "memory");
      flag_bad(live && !(t >= 9.094947017729282e-13f && t <= 1.329227995784916e36f));
    };
    auto step_scales = [&](Fin& f) {
#pragma unroll
      for (int c = 0; c < 4; c++)
        asm volatile("ld.shared.v4.u32 {%0, %1, %2, %3}, [%4];"
                     : "=r"(f.rp[4 * c]), "=r"(f.rp[4 * c + 1]), "=r"(f.rp[4 * c + 2]), "=r"(f.rp[4 * c + 3])
                     : "r"(sb + SM_RCP + wg * 320 + (lane & 3) * 80 + c * 16)
                     : "memory");
    };
    auto o_base = [&](uint32_t u) {
      return reinterpret_cast<char*>(g_o) + (size_t)((((prm.blk[u & 511] & 511u) * 4 + rank * 2) * 2 + wg) * (uint32_t)PANEL);
    };
    auto step_write = [&](const Fin& f, int lo, int hi) {
#pragma unroll
      for (int i = lo; i < hi; i++) {
        uint32_t v = __float_as_uint(s[i]);
        asm("mul.rn.bf16x2 %0, %0, %1;" : "+r"(v) : "r"(f.rp[(i % 28) >> 1]));
        s[i] = __uint_as_float(v);
        asm volatile("st.global.u32 [%0], %1;" ::"l"(f.dst + (i / 28) * 2 * PANEL + (i & 1) * 1792 + ((i % 28) >> 1) * 128), "r"(v) : "memory");
      }
    };
    auto keep_alive = [&](int lo, int hi, int c) {
      if (never == c) {
#pragma unroll
        for (int i = lo; i < hi; i++) asm volatile("st.shared.f32 [%0], %1;" ::"r"(stage + 4 * i), "f"(s[i]) : "memory");
        pin_order(never, c);
      }
    };
    auto step_signal = [&](int t) {
      __syncwarp();
      mbar_arrive1_if(sfull0 + 8 * (2 * t + wg), lane == 0);
    };
    auto free_panel = [&](int q) { mbar_arrive1_if(empty0 + 8 * (NSLOT + 4 * wg + q), tq < 2); };
    auto read_verdict = [&]() {
      uint32_t redo;
      asm volatile("ld.shared.u32 %0, [%1];" : "=r"(redo) : "r"(redo0 + 4 * wg) : "memory");
      return redo;
    };
    auto step_redo = [&](uint32_t prev) {
      asm volatile("" : "+r"(prev));
      bar_sync(3 + wg, 128);
      if (tq == 0) asm volatile("st.shared.u32 [%0], %1;" ::"r"(redo0 + 4 * wg), "r"(0) : "memory");
      const Unit u = decode_unit(prev & 511, rank);
      const int br = u.g >> 4, b = u.g & 15;
      const size_t off = (size_t)(b * kH + u.hc) * kSk * kDh;
      slow_rows(g_qrow + (blockIdx.x * 2 + wg) * (16 * 128) + tq, tq, prm.xp[br] + (b * kSq + wg * NQ) * kD, prm.wp[br] + u.hc * kDh,
                prm.kp[br] + off, prm.vp[br] + off, reinterpret_cast<__nv_bfloat16*>(o_base(prev)));
#pragma unroll
      for (int i = 0; i < 56; i++) s[i] = 0.f;
    };
    auto issue_slab = [&](uint32_t da, uint32_t db, int accum, auto split, auto tb) {
      constexpr int TB = tb.value, KS = TB ? 224 : 2;
      if (TB) db += 111 << 16;
      if (split.value == 1) {
#pragma unroll
        for (int t = 0; t < 2; t++) {
#pragma unroll
          for (int kk = 0; kk < 4; kk++) {
            if (t == 1 && kk == 2) bar_arrive(2 - wg, 256);
            wgmma_n112<1, 0, 1>(acc[t], da + t * 64 + kk * 256, db + kk * KS, 1);
          }
          wgmma_commit();
        }
      } else {
#pragma unroll
        for (int kk = 0; kk < 4; kk++) {
          if (kk == 3) bar_arrive(2 - wg, 256);
          wgmma_n112<1, TB>(acc[0], da + kk * 128, db + kk * KS, kk > 0 ? 1 : accum);
          wgmma_n112<1, TB>(acc[1], da + 512 + kk * 128, db + kk * KS, kk > 0 ? 1 : accum);
        }
        wgmma_commit();
      }
    };

    uint32_t code = head >> 23, prev = 0, pend = 0, uph = 0;
    uint32_t da = slot_desc(1), db = slot_desc(2 * wg);
    auto next_unit = [&](bool block) {
      da = slot_desc(it + 1), db = slot_desc(it + 2 * wg);
      if (block) {
        if (!__all_sync(0xffffffffu, probe(it + 1) & probe(it + 2 * wg))) {
          wait_full(it + 1);
          wait_full(it + 2 * wg);
        }
      }
    };
    wait_full(1);
    wait_full(2 * wg);
    for (int left = (head >> 10) & 31; left > 0; left--) {
      const int ui = u_end - left;
      uint32_t nxt;
      bool defer;
      auto peek = [&]() {
        const uint32_t cur = prm.unit[ui];
        nxt = __shfl_sync(0xffffffffu, (uint32_t)prm.unit[ui + 1], 0);
        defer = left > 1 && (!(nxt & 0x8000u) || ((cur & 0x8000u) ? unit_slabs(nxt) >= 10 : cur & 0x4000u));
      };
      const bool out = code & 0x8000u;
      uint32_t rel = 0;
      auto retire = [&]() {
        wgmma_wait<0>();
        fence_regs(acc[0]);
        fence_regs(acc[1]);
        mbar_arrive1_if(rel, rel);
        rel = 0;
      };
      auto turn = [&](int accum, auto mode, auto tb, auto first) {
        bar_sync(1 + wg, 256);
        if (!first.value) retire();
        wgmma_fence();
        issue_slab(da, db, accum, mode, tb);
      };
      auto take_turn = [&](int accum, auto mode, auto first) {
        if (out) turn(accum, mode, IntC<1>{}, first);
        else turn(accum, mode, IntC<0>{}, first);
      };
      Fin f;
      take_turn(0, IntC<0>{}, BoolC<true>{});
      int k = 0;
      const bool staged = pend == 2;
      if (out ? pend == 1 : !staged) {
        uint32_t redo = 0;
        static_for<0, 8>([&](auto kc) {
          constexpr int k = kc.value;
          if (k > 0) take_turn(1, IntC<0>{}, BoolC<false>{});
          if (k >= 4) keep_alive(w_cut(k - 4), w_cut(k - 3), 62 + 2 * k);
          if (k == 2) step_scales(f);
          constexpr int p0 = x_pos(0, k), p1 = x_pos(0, k + 1), o0 = x_off(0, k), o1 = x_off(0, k + 1);
          const uint32_t rw = empty0 + 8 * ring_slot(it + o0 + (p0 == 0));
          const uint32_t rx = empty0 + 8 * (p0 == 0 ? ring_slot(it + o0 + 2 * wg) : NSLOT + 4 * wg + p0 - 1);
          const uint32_t wi = it + o1 + (p1 == 0), xi = it + o1 + 2 * wg;
          const uint32_t xbar = full0 + 8 * (p1 == 0 ? ring_slot(xi) : NSLOT + 4 * wg + p1 - 1);
          const uint32_t xpar = (p1 == 0 ? ring_round(xi) : pph >> (p1 == 0 ? 0 : p1 - 1)) & 1;
          if constexpr (p1 != 0) pph ^= 1u << (p1 - 1);
          uint32_t okp = probe(wi) & test(xbar, xpar);
          if (k == 2) okp &= test(ok_bar, uph ^ pend);
          rel = pick(tq == 0, rw, pick(tq < 3 && (k < 6 || out), rx, 0));
          if (k == 0) {
            uint32_t a = rows_addr();
            asm volatile("" : "+r"(a), "+r"(okp), "+r"(rel));
            if (pend) step_sums();
            bar_sync(3 + wg, 128);
            rows_load(f, a);
          }
          if (k == 1) {
            mbar_arrive1_if(empty0 + 8 * (NSLOT + 4 * wg + 2), tq < 2 && pend);
            step_rows(f, pend);
          }
          if (k == 2) {
            step_finite(pend);
            f.dst = o_base(prev) + warp * 3584 + lane * 4;
          }
          if (k == 6) redo = read_verdict();
          if (k >= 3 && pend) step_write(f, w_cut(k - 3), w_cut(k - 2));
          if (k == 7) {
            if (__any_sync(0xffffffffu, redo)) step_redo(prev);
            __syncwarp();
            mbar_arrive1_if(sfull0 + 8 * (2 * lane + wg), lane < 2 && pend);
          }
          const bool ok = __all_sync(0xffffffffu, okp);
          da = slot_desc(wi);
          db = p1 == 0 ? slot_desc(xi) : dq + (p1 - 1) * (PANEL >> 4);
          if (!ok) {
            retire();
            wait_full(wi);
            mbar_wait_warp(xbar, xpar);
            if (k == 2) mbar_wait_warp(ok_bar, uph ^ pend);
          }
        });
        k = 8;
        if (out) turn(1, IntC<0>{}, IntC<1>{}, BoolC<false>{});
      }
      const int nslab = unit_slabs(code);
      uint32_t pos = k ? 3 : 0, wi = it + (k ? 12 : 1), xbar = full0 + 8 * (k ? NSLOT + 4 * wg + 2 : ring_slot(it + 2 * wg));
      const int kend = nslab - 2;
      if (k < kend) {
        uint32_t r = it + (k ? 13 : 3);
        const uint32_t pat = staged ? kPat1 : kPat0;
        const uint32_t keep_pos = out ? 3 : 1;
        const int keep_k = out ? nslab - 4 : 5;
#pragma unroll 1
        while (true) {
          rel = pick(tq == 0, empty0 + 8 * ring_slot(wi), pick(tq < 3 && (pos < keep_pos || k < keep_k), xbar + 8 * NBAR, 0));
          pos = next_pos(pos, k, pat);
          const bool ring = pos == 0;
          const uint32_t i = r + 2 * wg, q = pos - 1;
          wi = ring ? r + 1 : r;
          xbar = full0 + 8 * (ring ? ring_slot(i) : NSLOT + 4 * wg + q);
          const uint32_t xpar = (ring ? ring_round(i) : pph >> q) & 1;
          da = slot_desc(wi);
          db = ring ? slot_desc(i) : dq + q * (PANEL >> 4);
          pph ^= ring ? 0u : 1u << q;
          r += ring ? 3 : 1;
          const bool ok = __all_sync(0xffffffffu, probe(wi) & test(xbar, xpar));
          if (staged && k < 2) {
            if (k == 0) {
              store_half<1, 0, 4>(st_p, s);
            } else {
              store_half<1, 4, 7>(st_p, s);
              step_signal(1);
            }
          }
          if (!ok) {
            retire();
            wait_full(wi);
            mbar_wait_warp(xbar, xpar);
          }
          if (++k == kend) break;
          take_turn(1, IntC<0>{}, BoolC<false>{});
        }
      }
      it += nslab + (staged ? 8 : 4);
      const uint32_t ql = out ? 1 : 3, xl = full0 + 8 * (NSLOT + 4 * wg + ql), pl = pph >> ql & 1, dl = slot_desc(it - 1);
      pph ^= 1u << ql;
      if (!__all_sync(0xffffffffu, probe(it - 1) & test(xl, pl))) {
        retire();
        wait_full(it - 1);
        mbar_wait_warp(xl, pl);
      }
      auto last_turn = [&](auto tb) {
        constexpr int TB = tb.value;
        bar_sync(1 + wg, 256);
        retire();
        wgmma_fence();
#pragma unroll
        for (int t = 0; t < 2; t++) {
#pragma unroll
          for (int kk = 0; kk < 8; kk++)
            wgmma_n112<1, TB>(acc[t], (kk < 4 ? da : dl) + t * 512 + (kk & 3) * 128,
                              db + t * never + (TB ? 111 << 16 : 0) + (kk >> 2) * (PANEL >> 4) + (kk & 3) * (TB ? 224 : 2), 1);
          wgmma_commit();
        }
        bar_arrive(2 - wg, 256);
      };
      const uint32_t rw2 = empty0 + 8 * pick(tq == 0, ring_slot(it - 2), ring_slot(it - 1));
      if (!out) {
        {
          last_turn(IntC<0>{});
          keep_alive(28, 56, 80);
          const bool ok = __all_sync(0xffffffffu, probe(it));
          rel = pick(tq < 2, rw2, 0);
          da = slot_desc(it);
          wgmma_wait<1>();
          fence_regs(acc[0]);
          q_half<0>(st_q, s, acc[0], never);
          wgmma_wait<0>();
          fence_regs(acc[1]);
          q_half<1>(st_q, s, acc[1], never);
          mbar_arrive1_if(rel, rel);
          if (!ok) wait_full(it);
        }
        fence_async_smem();
        auto issue_s = [&](uint32_t dk, int accum) {
          wgmma_fence();
#pragma unroll
          for (int kk = 0; kk < 8; kk++)
            wgmma_n112<0, 0, 1>(s, dk + (kk >> 2) * 64 + (kk & 3) * 2, dq + (kk >> 2) * (PANEL >> 4) + (kk & 3) * 2, kk > 0 ? 1 : accum);
          wgmma_commit();
        };
        auto add_sums = [&]() {
#pragma unroll
          for (int jj = 0; jj < 14; jj++)
            asm volatile("{\n.reg .b32 t;\nshl.b32 t, %2, 16;\nadd.f32 %0, %0, t;\nand.b32 t, %2, 0xffff0000;\nadd.f32 %1, %1, t;\n}"
                         : "+f"(l[2 * jj]), "+f"(l[2 * jj + 1])
                         : "r"(ps[jj]));
        };
        auto softmax = [&](uint32_t par, int pin0) {
          const uint32_t pa = st_p + par * PANEL;
#pragma unroll
          for (int i = 0; i < 4 + SM_OFF; i++) s[i] = ex2(s[i]);
#pragma unroll
          for (int jj = 0; jj < 14; jj++) {
#pragma unroll
            for (int i = 4 * jj + 4 + SM_OFF; i < 4 * jj + 8 + SM_OFF; i++)
              if (i < 56) s[i] = ex2(s[i]);
            const uint32_t p0 = pack_bf16(s[4 * jj], s[4 * jj + 1]), p1 = pack_bf16(s[4 * jj + 2], s[4 * jj + 3]);
            stsm_x2_t_pin(pa + jj * 1024, p0, p1, never, pin0);
            s[4 * jj] = __uint_as_float(p0), s[4 * jj + 1] = __uint_as_float(p1);
            asm("add.rn.bf16x2 %0, %1, %2;" : "=r"(ps[jj]) : "r"(p0), "r"(p1));
          }
        };
        bar_sync(1 + wg, 256);
        issue_s(da, never);
        bar_arrive(2 - wg, 256);
        {
#pragma unroll
          for (int i = 0; i < 28; i++) asm volatile("mov.b32 %0, 0;" : "=f"(l[i]));
          peek();
          const bool ok = __all_sync(0xffffffffu, probe(it + 1));
          da = slot_desc(it + 1);
          wgmma_wait_pin<0>(never, 180);
          fence_regs(s);
          release(it);
          softmax(0, 176);
          if (!ok) wait_full(it + 1);
        }
        it += 1;
#pragma unroll 1
        for (int j = 1; j < 16; j++) {
          fence_async_smem();
          bar_sync(1 + wg, 256);
          issue_s(da, 0);
          pin_order(never, 2 * j + 128);
          const uint32_t okv = mbar_test(full0 + 8 * ring_slot(it + 1), ring_par(it + 1));
          const uint32_t okk = probe(it + 2);
          da = slot_desc(it + 2);
          add_sums();
          const bool ok = __all_sync(0xffffffffu, okk);
          if (!__all_sync(0xffffffffu, okv)) wait_full(it + 1);
          {
            const uint32_t dv = slot_desc(it + 1), dp = dq + (3 - (j & 1)) * (PANEL >> 4);
            wgmma_fence();
#pragma unroll
            for (int kk = 0; kk < 4; kk++) {
              wgmma_n112<1, 0, 1>(acc[0], dv + kk * 256, dp + kk * 2, kk > 0 ? 1 : j > 1);
              wgmma_n112<1, 0, 1>(acc[1], dv + 64 + kk * 256, dp + kk * 2, kk > 0 ? 1 : j > 1);
            }
          }
          wgmma_commit();
          bar_arrive(2 - wg, 256);
          wgmma_wait<1>();
          fence_regs(s);
          release(it);
          softmax(j & 1, 2 * j + 192);
          wgmma_wait<0>();
          fence_regs(acc[0]);
          fence_regs(acc[1]);
          release(it + 1);
          it += 2;
          if (!ok) {
            wait_full(it);
          }
        }
        it += 1;
        fence_async_smem();
        bar_sync(1 + wg, 256);
        wgmma_fence();
        issue_slab(da, dq + 3 * (PANEL >> 4), 1, IntC<1>{}, IntC<0>{});
        pin_order(never, 182);
        mbar_arrive1_if(empty0 + 8 * (NSLOT + 4 * wg + (tq >> 1)), tq < 4);
        rel = pick(tq == 0, empty0 + 8 * ring_slot(it - 1), pick(tq < 3, empty0 + 8 * (NSLOT + 4 * wg + 3), 0));
        next_unit(defer);
        if (defer) {
          wgmma_wait<1>();
          fence_regs(acc[0]);
          pack_half<0>(s, acc[0]);
          fence_half<0>(s);
          wgmma_wait_pin<0>(never, 172);
          fence_regs(acc[1]);
          mbar_arrive1_if(rel, rel);
          pack_half<1>(s, acc[1]);
        }
        pend = 1;
      } else {
        last_turn(IntC<1>{});
        pin_order(never, 186);
        peek();
#pragma unroll
        for (int i = 0; i < 28; i++) ps[i >> 1] = 0, l[i] = 0.f;
        mbar_wait_warp(ok_bar, uph);
        next_unit(defer);
        rel = pick(tq < 2, rw2, pick(tq < 6, empty0 + 8 * (NSLOT + 4 * wg - 1 + (tq >> 1)), 0));
        wgmma_wait<1>();
        fence_regs(acc[0]);
        pack_half<0>(s, acc[0]);
        store_half<0>(st_p, s);
        step_signal(0);
        wgmma_wait<0>();
        fence_regs(acc[1]);
        mbar_arrive1_if(rel, rel);
        pack_half<1>(s, acc[1]);
        pend = 2;
      }
      if (!defer) {
        if (pend == 2) {
          store_half<1>(st_p, s);
        } else {
          step_sums();
          bar_sync(3 + wg, 128);
          rows_load(f, rows_addr());
          f.dst = o_base(code) + warp * 3584 + lane * 4;
          mbar_wait_warp(ok_bar, uph);
          step_rows(f, true);
          bar_sync(3 + wg, 128);
          step_scales(f);
          free_panel(2);
          retire();
          pack_half<0>(s, acc[0]);
          pack_half<1>(s, acc[1]);
          step_finite(true);
          step_write(f, 0, 28);
          bar_sync(3 + wg, 128);
          const uint32_t redo = read_verdict();
          step_write(f, 28, 56);
          if (__any_sync(0xffffffffu, redo)) step_redo(code);
          step_signal(0);
        }
        step_signal(1);
        pend = 0;
#pragma unroll
        for (int i = 0; i < 28; i++) ps[i >> 1] = 0, l[i] = 0.f;
        if (left > 1) {
          wait_full(it + 1);
          wait_full(it + 2 * wg);
        }
      }
      prev = code, code = nxt, uph ^= 1;
    }
    if (wg == 0) bar_sync(1, 256);
  }
}

typedef CUresult (*EncodeFn)(CUtensorMap*, CUtensorMapDataType, cuuint32_t, void*, const cuuint64_t*, const cuuint64_t*,
                             const cuuint32_t*, const cuuint32_t*, CUtensorMapInterleave, CUtensorMapSwizzle,
                             CUtensorMapL2promotion, CUtensorMapFloatOOBfill);

bool encode(EncodeFn fn, CUtensorMap* m, const void* ptr, int rank, const cuuint64_t* dims, const cuuint64_t* strides,
            const cuuint32_t* box, CUtensorMapL2promotion promo, CUtensorMapSwizzle swz = CU_TENSOR_MAP_SWIZZLE_128B) {
  const cuuint32_t es[4] = {1, 1, 1, 1};
  return fn(m, CU_TENSOR_MAP_DATA_TYPE_BFLOAT16, rank, const_cast<void*>(ptr), dims, strides, box, es,
            CU_TENSOR_MAP_INTERLEAVE_NONE, swz, promo,
            CU_TENSOR_MAP_FLOAT_OOB_FILL_NONE) == CUDA_SUCCESS;
}
bool encode_panels(EncodeFn fn, CUtensorMap* m, const void* ptr, uint64_t rows, uint64_t cols, uint32_t box_rows,
                   uint32_t box_blocks = 2) {
  const cuuint64_t dims[3] = {64, rows, cols / 64};
  const cuuint64_t strides[2] = {cols * 2, 128};
  const cuuint32_t box[3] = {64, box_rows, box_blocks};
  CUtensorMapL2promotion promo = CU_TENSOR_MAP_L2_PROMOTION_L2_128B;
  return encode(fn, m, ptr, 3, dims, strides, box, promo);
}
bool encode_kv(EncodeFn fn, CUtensorMap* m, const void* ptr) {
  const cuuint64_t dims[4] = {64, 8, 2, (uint64_t)kB * kH * kSk / 8};
  const cuuint64_t strides[3] = {kDh * 2, 128, 8 * kDh * 2};
  const cuuint32_t box[4] = {64, 8, 2, 8};
  CUtensorMapL2promotion promo = CU_TENSOR_MAP_L2_PROMOTION_L2_128B;
  return encode(fn, m, ptr, 4, dims, strides, box, promo);
}
bool encode_2d(EncodeFn fn, CUtensorMap* m, const void* ptr, uint64_t rows, uint64_t cols, uint32_t box_rows,
               CUtensorMapSwizzle swz = CU_TENSOR_MAP_SWIZZLE_128B) {
  const cuuint64_t dims[2] = {cols, rows};
  const cuuint64_t strides[1] = {cols * 2};
  const cuuint32_t box[2] = {64, box_rows};
  CUtensorMapL2promotion promo = CU_TENSOR_MAP_L2_PROMOTION_L2_128B;
  return encode(fn, m, ptr, 2, dims, strides, box, promo, swz);
}

constexpr int kTunedPairs = 66;
const uint16_t kTunedBlock[kAttnUnits] = {
    20480, 20486, 20492, 20498, 20504, 20510, 20516, 20522, 20528, 20534, 16444, 16450, 16456, 16462, 20996, 21002,
    20481, 20487, 20493, 20499, 20505, 20511, 20517, 20523, 20529, 20535, 16445, 16451, 16457, 16463, 20997, 21003,
    20482, 20488, 20494, 20500, 20506, 20512, 20518, 20524, 20530, 20536, 16446, 16452, 16458, 20992, 20998, 21004,
    20483, 20489, 20495, 20501, 20507, 20513, 20519, 20525, 20531, 20537, 16447, 16453, 16459, 20993, 20999, 21005,
    20484, 20490, 20496, 20502, 20508, 20514, 20520, 20526, 20532, 20538, 16448, 16454, 16460, 20994, 21000, 21006,
    20485, 20491, 20497, 20503, 20509, 20515, 20521, 20527, 20533, 20539, 16449, 16455, 16461, 20995, 21001, 21007,
    21008, 21012, 21016, 21020, 21024, 21028, 21032, 21036, 21040, 21044, 21048, 16956, 16960, 16964, 16968, 16972,
    21009, 21013, 21017, 21021, 21025, 21029, 21033, 21037, 21041, 21045, 21049, 16957, 16961, 16965, 16969, 16973,
    21010, 21014, 21018, 21022, 21026, 21030, 21034, 21038, 21042, 21046, 21050, 16958, 16962, 16966, 16970, 16974,
    21011, 21015, 21019, 21023, 21027, 21031, 21035, 21039, 21043, 21047, 21051, 16959, 16963, 16967, 16971, 16975,
    21504, 21506, 21508, 21510, 21512, 21514, 21516, 21518, 21520, 21522, 21524, 21526, 21528, 21530, 21532, 21534,
    21505, 21507, 21509, 21511, 21513, 21515, 21517, 21519, 21521, 21523, 21525, 21527, 21529, 21531, 21533, 21535,
    21536, 21540, 21544, 21548, 21552, 21556, 21560, 17468, 17472, 17476, 17480, 17484, 22016, 22020, 22024, 22028,
    21537, 21541, 21545, 21549, 21553, 21557, 21561, 17469, 17473, 17477, 17481, 17485, 22017, 22021, 22025, 22029,
    21538, 21542, 21546, 21550, 21554, 21558, 21562, 17470, 17474, 17478, 17482, 17486, 22018, 22022, 22026, 22030,
    21539, 21543, 21547, 21551, 21555, 21559, 21563, 17471, 17475, 17479, 17483, 17487, 22019, 22023, 22027, 22031,
    22032, 22034, 22036, 22038, 22040, 22042, 22044, 22046, 22048, 22050, 22052, 22054, 22056, 22058, 22060, 22062,
    22033, 22035, 22037, 22039, 22041, 22043, 22045, 22047, 22049, 22051, 22053, 22055, 22057, 22059, 22061, 22063,
    22064, 22066, 22068, 22070, 22072, 22074, 17980, 17982, 17984, 17986, 17988, 17990, 17992, 17994, 17996, 17998,
    22065, 22067, 22069, 22071, 22073, 22075, 17981, 17983, 17985, 17987, 17989, 17991, 17993, 17995, 17997, 17999,
    22528, 22529, 22530, 22531, 22532, 22533, 22534, 22535, 22536, 22537, 22538, 22539, 22540, 22541, 22542, 22543,
    22544, 22545, 22546, 22547, 22548, 22549, 22550, 22551, 22552, 22553, 22554, 22555, 22556, 22557, 22558, 22559,
    22560, 22570, 22580, 4178, 4188, 4198, 4208, 4218, 4228, 4238, 4248, 4258, 4268, 4278, 4288, 4298,
    22561, 22571, 22581, 4179, 4189, 4199, 4209, 4219, 4229, 4239, 4249, 4259, 4269, 4279, 4289, 4299,
    22562, 22572, 22582, 4180, 4190, 4200, 4210, 4220, 4230, 4240, 4250, 4260, 4270, 4280, 4290, 4300,
    22563, 22573, 22583, 4181, 4191, 4201, 4211, 4221, 4231, 4241, 4251, 4261, 4271, 4281, 4291, 4301,
    22564, 22574, 22584, 4182, 4192, 4202, 4212, 4222, 4232, 4242, 4252, 4262, 4272, 4282, 4292, 4302,
    22565, 22575, 22585, 4183, 4193, 4203, 4213, 4223, 4233, 4243, 4253, 4263, 4273, 4283, 4293, 4303,
    22566, 22576, 22586, 4184, 4194, 4204, 4214, 4224, 4234, 4244, 4254, 4264, 4274, 4284, 4294, 4304,
    22567, 22577, 22587, 4185, 4195, 4205, 4215, 4225, 4235, 4245, 4255, 4265, 4275, 4285, 4295, 4305,
    22568, 22578, 4176, 4186, 4196, 4206, 4216, 4226, 4236, 4246, 4256, 4266, 4276, 4286, 4296, 4306,
    22569, 22579, 4177, 4187, 4197, 4207, 4217, 4227, 4237, 4247, 4257, 4267, 4277, 4287, 4297, 4307};
const uint8_t kTunedLen[kTunedPairs] = {
    10, 10, 10, 10, 10, 10, 10, 9, 9, 11, 9, 11, 10, 10, 10, 10, 8, 9, 11, 8, 9, 10, 10, 11, 9, 9, 10, 10, 11, 10, 10, 11, 9,
    9, 10, 9, 9, 11, 10, 10, 9, 10, 11, 10, 10, 10, 10, 10, 9, 11, 10, 10, 10, 9, 10, 10, 10, 9, 10, 11, 10, 9, 10, 10, 9, 10};
const uint8_t kTunedDelay[kTunedPairs] = {
    0, 0, 0, 0, 0, 29, 5, 0, 105, 1, 0, 0, 1, 0, 1, 0, 0, 0, 0, 109, 109, 29,
    0, 0, 15, 111, 0, 31, 3, 7, 1, 0, 0, 105, 7, 72, 0, 0, 0, 0, 0, 1, 7, 0,
    0, 23, 5, 1, 0, 3, 1, 3, 0, 0, 7, 13, 0, 0, 0, 17, 35, 0, 0, 0, 115, 0};
const uint16_t kTunedUnit[] = {
    0, 37388, 178, 231, 266, 328, 403, 441, 8655, 55809, 50, 47, 140, 242, 239, 313, 416, 422,
    16860, 58511, 37, 93, 123, 210, 223, 297, 400, 406, 25036, 58375, 81, 95, 16508, 39177, 220, 293,
    348, 437, 16891, 60031, 52, 30, 153, 240, 24782, 48396, 417, 439, 16877, 62127, 25, 36870, 149, 170,
    235, 16691, 49471, 375, 25005, 61445, 71, 34053, 100, 179, 200, 269, 336, 388, 25018, 64778, 64, 38156,
    177, 230, 263, 16710, 51469, 54538, 53767, 26, 132, 180, 248, 286, 335, 372, 25002, 57866, 70, 129,
    110, 211, 255, 45057, 317, 497, 376, 16814, 58047, 18, 32775, 16509, 40207, 16662, 49679, 469, 16780, 53903,
    5, 31, 154, 16625, 43522, 47113, 301, 465, 503, 16782, 54719, 38, 13, 121, 224, 253, 295, 352,
    358, 24988, 57351, 36, 79, 16539, 41999, 45316, 16680, 49279, 484, 16779, 61551, 6, 78, 137, 192, 43583,
    316, 449, 487, 24958, 63492, 35, 15, 16522, 41231, 47621, 299, 369, 359, 24989, 58630, 16, 33039, 167,
    233, 271, 16724, 52495, 57615, 66, 33295, 183, 202, 288, 16726, 52231, 473, 495, 69, 63, 16491, 38367,
    245, 259, 49158, 480, 470, 24941, 53254, 16426, 33855, 187, 16620, 46351, 434, 25048, 61709, 58, 16485, 38922,
    218, 305, 341, 468, 24955, 61961, 41, 115, 160, 197, 273, 16684, 51717, 499, 16778, 62559, 83, 46,
    105, 16592, 44335, 303, 386, 424, 16862, 62911, 1, 91, 16534, 38111, 229, 274, 302, 354, 392, 25022,
    53508, 72, 145, 16526, 41487, 282, 329, 419, 457, 479, 74, 148, 181, 217, 287, 337, 404, 25050,
    62730, 34, 92, 152, 193, 16606, 48143, 498, 377, 399, 51695, 57, 37900, 162, 199, 280, 16707, 51207,
    471, 24942, 64516, 7, 16459, 37263, 184, 250, 16673, 48607, 496, 486, 24957, 55302, 24, 128, 157, 24771,
    44038, 283, 331, 451, 25081, 59403, 22, 96, 139, 225, 238, 311, 368, 374, 16812, 52367, 67, 76,
    120, 16575, 39103, 277, 16704, 49410, 420, 25066, 56330, 48, 35343, 168, 247, 284, 332, 467, 16746, 53599,
    10, 116, 164, 216, 285, 334, 356, 16794, 63752, 40, 97, 126, 227, 256, 314, 448, 454, 16892,
    60815, 89, 131, 176, 214, 16645, 50447, 16837, 62468, 56623, 84, 77, 16490, 39439, 279, 325, 371, 409,
    431, 49, 43, 16502, 36063, 213, 258, 318, 370, 408, 25038, 54276, 20, 29, 103, 188, 252, 309,
    349, 485, 24940, 64007, 17, 35852, 161, 215, 281, 324, 355, 393, 415, 61935, 19, 59, 16518, 39951,
    262, 322, 482, 361, 383, 85, 16395, 32911, 165, 16616, 46095, 433, 455, 509, 55743, 87, 98, 158,
    243, 43009, 45571, 268, 333, 483, 24954, 55562, 53, 16497, 36991, 185, 203, 290, 343, 500, 16795, 51823,
    2, 12, 135, 16558, 43279, 321, 450, 488, 8559, 56577, 9, 99, 159, 244, 257, 315, 385, 391,
    16829, 63903, 55, 16412, 34159, 186, 204, 308, 347, 421, 16875, 58751, 54, 61, 119, 173, 205, 294,
    16734, 51343, 16842, 54367, 80, 34831, 166, 16633, 45103, 464, 423, 16861, 60575, 39, 112, 16525, 37599, 198,
    16644, 47727, 481, 360, 414, 64959, 86, 94, 156, 194, 16638, 45647, 401, 407, 25037, 59654, 23, 44,
    16492, 42255, 16649, 47279, 353, 502, 24973, 59910, 21, 45, 151, 189, 221, 310, 351, 501, 24956, 60679,
    65, 35087, 182, 201, 270, 339, 452, 16747, 63583, 8, 130, 127, 16580, 41167, 16660, 50191, 389, 25035,
    60424, 56, 114, 111, 212, 272, 298, 432, 438, 16876, 64143, 51, 144, 109, 226, 207, 312, 384,
    390, 16828, 57487, 32, 36111, 40971, 219, 306, 344, 357, 16811, 53375, 82, 62, 122, 16593, 43055, 45407,
    418, 456, 510, 59599, 88, 146, 143, 228, 44289, 275, 319, 402, 440, 16878, 56511, 16457, 33794, 147,
    163, 246, 264, 327, 387, 425, 447, 68, 14, 136, 190, 16621, 47375, 466, 16888, 55855, 33, 27,
    102, 172, 44159, 291, 345, 373, 16827, 55423, 4, 37127, 133, 171, 251, 292, 346, 405, 16859, 59775,
    90, 117, 169, 234, 304, 338, 436, 16890, 64607, 3, 60, 104, 16559, 39343, 267, 330, 435, 489,
    511};
void build_schedule(Params& prm, int pairs) {
  for (int i = 0; i < kAttnUnits; i++) prm.blk[i] = (uint16_t)(i | 1 << 12);
  uint8_t delay[kMaxPairs] = {};
  static uint16_t lists[kMaxPairs][kMaxUnits];
  int n[kMaxPairs] = {};
  double t[kMaxPairs] = {};
  const double ta = 40.0, to = 59.0;
  for (int u = 0; u < kUnits; u++) {
    int p = 0;
    for (int q = 1; q < pairs; q++)
      if (t[q] < t[p] - 1e-9) p = q;
    uint16_t code;
    if (u < kAttnUnits) {
      code = (uint16_t)u;
    } else {
      const int o = u - kAttnUnits, g2 = o / 5, r = o % 5;
      code = (uint16_t)(0x800F | (r < 4 ? ((2 * g2 + (r >> 1)) << 2) | (r & 1) : ((2 * g2) << 2) | 2) << 8);
    }
    lists[p][n[p]++] = code;
    t[p] += u < kAttnUnits ? ta : to;
  }
  if (pairs == kTunedPairs) {
    for (int p = 0, o = 0; p < pairs; p++) {
      n[p] = kTunedLen[p];
      delay[p] = kTunedDelay[p];
      for (int i = 0; i < n[p]; i++) lists[p][i] = kTunedUnit[o++];
    }
    for (int i = 0; i < kAttnUnits; i++) prm.blk[i] = kTunedBlock[i];
  }
  int o = 0;
  for (int p = 0; p < pairs; p++) {
    prm.head[p] = o | n[p] << 10 | delay[p] << 15 | (uint32_t)(lists[p][0] & 511) << 23;
    for (int i = 0; i < n[p]; i++) prm.unit[o++] = lists[p][i];
  }
}

}

extern "C" void kernel_launch(void* const* d_in, const int* in_sizes, int n_in, void* d_out, int out_size) {
  (void)in_sizes; (void)n_in; (void)out_size;
  void* fnp = nullptr;
  cudaDriverEntryPointQueryResult qr;
  if (cudaGetDriverEntryPoint("cuTensorMapEncodeTiled", &fnp, cudaEnableDefault, &qr) != cudaSuccess || !fnp) return;
  EncodeFn fn = (EncodeFn)fnp;
  void* optr = nullptr;
  cudaGetSymbolAddress(&optr, g_o);
  Params prm;
  bool ok = true;
  for (int br = 0; br < 2; br++) {
    void* const* in = d_in + 5 * br;
    ok &= encode_2d(fn, &prm.x[br], in[0], (uint64_t)kB * kSq, kD, NQ);
    ok &= encode_kv(fn, &prm.kv[br], in[1]);
    ok &= encode_kv(fn, &prm.kv[2 + br], in[2]);
    ok &= encode_panels(fn, &prm.wq[br], in[3], kD, kH * kDh, 64);
    ok &= encode_panels(fn, &prm.wo[br], in[4], kH * kDh, kD, 64);
    prm.xp[br] = (const __nv_bfloat16*)in[0];
    prm.wp[br] = (const __nv_bfloat16*)in[3];
    prm.kp[br] = (const __nv_bfloat16*)in[1];
    prm.vp[br] = (const __nv_bfloat16*)in[2];
  }
  prm.op = (__nv_bfloat16*)d_out;
  ok &= encode_2d(fn, &prm.o_ld, optr, (uint64_t)kAttnUnits * 4 * kSq, 64, NQ, CU_TENSOR_MAP_SWIZZLE_NONE);
  ok &= encode_panels(fn, &prm.out, d_out, (uint64_t)kB * kSq, 2 * kD, ST_ROWS, 1);
  if (!ok) return;
  cudaFuncSetAttribute(mha_fused_kernel, cudaFuncAttributeMaxDynamicSharedMemorySize, SMEM_BYTES);
  cudaLaunchConfig_t cfg = {};
  cfg.gridDim = dim3(2);
  cfg.blockDim = dim3(384);
  cfg.dynamicSmemBytes = SMEM_BYTES;
  cfg.stream = cudaStreamPerThread;
  int pairs = 0;
  if (cudaOccupancyMaxActiveClusters(&pairs, mha_fused_kernel, &cfg) != cudaSuccess || pairs < 1) return;
  if (pairs > kMaxPairs) pairs = kMaxPairs;
  if (pairs < 24) return;
  build_schedule(prm, pairs);
  mha_fused_kernel<<<2 * pairs, 384, SMEM_BYTES, cudaStreamPerThread>>>(prm);
}
```

```cpp
#include <cuda_runtime.h>
#include <cuda_bf16.h>
#include <cuda.h>
#include <stdint.h>

namespace {

constexpr int kB = 16, kSq = 224, kD = 640, kH = 32, kSk = 1024, kDh = 128;
constexpr int kGroups = 2 * kB;
constexpr int kAttnUnits = kGroups * kH / 2;
constexpr int kOutUnits = kGroups * 5 / 2;
constexpr int kUnits = kAttnUnits + kOutUnits;
constexpr int kMaxUnits = kUnits + 64;
constexpr int kMaxPairs = 72;
constexpr int NQ = 112;
constexpr int PANEL = NQ * 128;
constexpr float kQScale = 0.08838834764831845f * 1.4426950408889634f;
constexpr int SLOT = 16384;
constexpr int NSLOT = 7;

constexpr int SM_PANEL = 0;
constexpr int SM_RING = SM_PANEL + 8 * PANEL;
constexpr int NBAR = NSLOT + 8;
constexpr int SM_RCP = SM_RING + NSLOT * SLOT;
constexpr int SM_BAR = SM_RCP + 640;
constexpr int SM_END = SM_BAR + 8 * (2 * NBAR + 12) + 32;
constexpr int SMEM_BYTES = SM_END + 1024;
static_assert(SM_RING % 1024 == 0 && PANEL % 1024 == 0, "swizzle alignment");
static_assert(SMEM_BYTES <= 232448, "smem");

struct Params {
  CUtensorMap x[2], wq[2], kv[4], wo[2];
  CUtensorMap o_ld, out;
  const __nv_bfloat16* xp[2];
  const __nv_bfloat16* wp[2];
  const __nv_bfloat16* kp[2];
  const __nv_bfloat16* vp[2];
  __nv_bfloat16* op;
  uint32_t head[kMaxPairs];
  uint16_t unit[kMaxUnits];
  uint16_t blk[kAttnUnits];
};

struct Unit {
  bool attn, mc;
  int g, hc;
  int h0, nslab;
};
__device__ __forceinline__ int unit_slabs(uint32_t u) {
  return (u & 0x8000u) ? 4 * ((u & 15) + 1 - ((u >> 4) & 15)) : kD / 64;
}
__device__ __forceinline__ Unit decode_unit(uint32_t u, uint32_t rank) {
  Unit r;
  r.attn = !(u & 0x8000u);
  r.nslab = unit_slabs(u);
  if (r.attn) {
    r.g = (u >> 4) & 31;
    r.hc = (u & 15) * 2 + rank;
    r.mc = true;
    r.h0 = 0;
  } else {
    const uint32_t t = (u >> 8) & 3;
    r.mc = t < 2;
    r.g = ((u >> 10) & 31) + (t < 2 ? 0 : rank);
    r.hc = t < 2 ? 2 * t + rank : 4;
    r.h0 = (u >> 4) & 15;
  }
  return r;
}

__device__ uint4 g_qrow[2 * kMaxPairs * 2 * 16 * 128];
__device__ unsigned int g_pc[128 * 16 * 2];
__device__ __nv_bfloat16 g_o[(size_t)kAttnUnits * kSq * 2 * kDh];
__device__ unsigned int g_ticket;
__device__ unsigned int g_rd[kAttnUnits];
__device__ unsigned int g_cnt[kAttnUnits];

constexpr int CREGS = 232, SM_OFF = -1, Q_PIN = 0x15, ST_ROWS = 56;
template <bool V>
struct BoolC {
  static constexpr bool value = V;
};
template <int V>
struct IntC {
  static constexpr int value = V;
};
template <int I, int N, class F>
__device__ __forceinline__ void static_for(F&& f) {
  if constexpr (I < N) {
    f(IntC<I>{});
    static_for<I + 1, N>(f);
  }
}
constexpr uint32_t kPat0 = 04321432100, kPat1 = 04302102100;
__host__ __device__ constexpr int x_pos(int pat, int k) { return ((pat == 0 ? kPat0 : kPat1) >> 3 * k) & 7; }
__host__ __device__ constexpr int x_off(int pat, int k) { return k == 0 ? 0 : x_off(pat, k - 1) + (x_pos(pat, k - 1) == 0 ? 3 : 1); }
__host__ __device__ constexpr int w_cut(int i) { return 56 * i / 5; }
__device__ __forceinline__ uint32_t unit_pattern(uint32_t u, uint32_t prev) {
  return (prev & 0x8000u) && unit_slabs(u) >= 10 ? kPat1 : kPat0;
}
__device__ __forceinline__ uint32_t next_pos(uint32_t pos, int k, uint32_t pat) {
  return k < 9 ? (pat >> (3 * k + 3)) & 7 : (pos & 3) + 1;
}
__device__ __forceinline__ uint32_t pick(bool c, uint32_t a, uint32_t b) {
  uint32_t r;
  asm("{\n.reg .pred p;\nsetp.ne.u32 p, %1, 0;\nselp.u32 %0, %2, %3, p;\n}" : "=r"(r) : "r"((uint32_t)c), "r"(a), "r"(b));
  return r;
}
__device__ __forceinline__ uint32_t ring_round(uint32_t i) { return (i * 9363u) >> 16; }
__device__ __forceinline__ uint32_t ring_slot(uint32_t i) { return i - NSLOT * ring_round(i); }
__device__ __forceinline__ uint32_t ring_par(uint32_t i) { return ring_round(i) & 1; }

__device__ __forceinline__ uint32_t smem_u32(const void* p) { return (uint32_t)__cvta_generic_to_shared(p); }
__device__ __forceinline__ void mbar_init(uint32_t bar, uint32_t cnt) {
  asm volatile("mbarrier.init.shared::cta.b64 [%0], %1;" ::"r"(bar), "r"(cnt));
}
__device__ __forceinline__ void mbar_arrive1_if(uint32_t bar, bool pred) {
  asm volatile("{\n.reg .pred p;\nsetp.ne.u32 p, %1, 0;\n@p mbarrier.arrive.shared::cta.b64 _, [%0];\n}" ::"r"(bar), "r"((uint32_t)pred)
               : "memory");
}
__device__ __forceinline__ void mbar_wait_warp(uint32_t bar, uint32_t parity) {
  asm volatile(
      "{\n.reg .pred p, q;\n.reg .u32 c;\n"
      "mov.u32 c, 0;\n"
      "SPIN:\n"
      "mbarrier.try_wait.parity.shared::cta.b64 p, [%0], %1;\n"
      "vote.sync.all.pred q, p, 0xffffffff;\n"
      "@q bra.uni DONE;\n"
      "add.u32 c, c, 1;\n"
      "setp.gt.u32 q, c, 0x1000000;\n"
      "@q trap;\n"
      "bra.uni SPIN;\n"
      "DONE:\n}" ::"r"(bar),
      "r"(parity)
      : "memory");
}
__device__ __forceinline__ uint32_t mbar_test(uint32_t bar, uint32_t parity) {
  uint32_t ok;
  asm volatile(
      "{\n.reg .pred p;\nmbarrier.test_wait.parity.shared::cta.b64 p, [%1], %2;\nselp.u32 %0, 1, 0, p;\n}"
      : "=r"(ok)
      : "r"(bar), "r"(parity)
      : "memory");
  return ok;
}
__device__ __forceinline__ uint32_t mbar_test_if(uint32_t bar, uint32_t parity, bool pred) {
  uint32_t ok;
  asm volatile(
      "{\n.reg .pred p, q;\nsetp.ne.u32 q, %3, 0;\nsetp.eq.u32 p, %3, 0;\n"
      "@q mbarrier.test_wait.parity.shared::cta.b64 p, [%1], %2;\nselp.u32 %0, 1, 0, p;\n}"
      : "=r"(ok)
      : "r"(bar), "r"(parity), "r"((uint32_t)pred)
      : "memory");
  return ok;
}
#define ELECTED "{\n.reg .pred e;\nelect.sync _|e, 0xffffffff;\n@e "
constexpr uint64_t kEvictFirst = 0x12F0000000000000ull, kEvictNormal = 0x1000000000000000ull;
__device__ __forceinline__ void flag_wait(const unsigned int* p, uint32_t target) {
  asm volatile(
      "{\n.reg .pred p, q;\n.reg .u32 c, v;\n"
      "mov.u32 c, 0;\n"
      "SPIN:\n"
      "ld.acquire.gpu.global.u32 v, [%0];\n"
      "setp.ge.u32 p, v, %1;\n"
      "vote.sync.all.pred q, p, 0xffffffff;\n"
      "@q bra.uni DONE;\n"
      "nanosleep.u32 200;\n"
      "add.u32 c, c, 1;\n"
      "setp.gt.u32 q, c, 0x1000000;\n"
      "@q trap;\n"
      "bra.uni SPIN;\n"
      "DONE:\n}" ::"l"(p),
      "r"(target)
      : "memory");
}
__device__ __forceinline__ uint32_t flags_wait(const unsigned int* p, uint32_t target, uint32_t need) {
  uint32_t m;
  asm volatile(
      "{\n.reg .pred p, q;\n.reg .u32 c, v;\n"
      "mov.u32 c, 0;\n"
      "SPIN:\n"
      "ld.acquire.gpu.global.u32 v, [%1];\n"
      "setp.ge.u32 p, v, %2;\n"
      "vote.sync.ballot.b32 %0, p, 0xffffffff;\n"
      "and.b32 v, %0, %3;\n"
      "setp.eq.u32 q, v, %3;\n"
      "@q bra.uni DONE;\n"
      "add.u32 c, c, 1;\n"
      "setp.gt.u32 q, c, 0x1000000;\n"
      "@q trap;\n"
      "bra.uni SPIN;\n"
      "DONE:\n"
      "fence.proxy.async.global;\n}"
      : "=&r"(m)
      : "l"(p), "r"(target), "r"(need)
      : "memory");
  return m;
}
__device__ __forceinline__ void e_arrive(uint32_t bar, uint32_t n) {
  asm volatile(ELECTED "mbarrier.arrive.shared::cta.b64 _, [%0], %1;\n}" ::"r"(bar), "r"(n) : "memory");
}
__device__ __forceinline__ void e_expect_tx(uint32_t bar, uint32_t bytes) {
  asm volatile(ELECTED "mbarrier.arrive.expect_tx.shared::cta.b64 _, [%0], %1;\n}" ::"r"(bar), "r"(bytes) : "memory");
}
__device__ __forceinline__ void tma_ld2(uint32_t dst, const CUtensorMap* m, int c0, int c1, uint32_t bar, uint64_t pol) {
  asm volatile(ELECTED
               "cp.async.bulk.tensor.2d.shared::cluster.global.mbarrier::complete_tx::bytes.L2::cache_hint [%0], [%1, {%3, %4}], "
               "[%2], %5;\n}" ::"r"(dst),
               "l"(m), "r"(bar), "r"(c0), "r"(c1), "l"(pol)
               : "memory");
}
__device__ __forceinline__ void tma_ld2_mc(uint32_t dst, const CUtensorMap* m, int c0, int c1, uint32_t bar, uint64_t pol) {
  asm volatile(ELECTED
               "cp.async.bulk.tensor.2d.shared::cluster.global.mbarrier::complete_tx::bytes.multicast::cluster.L2::cache_hint "
               "[%0], [%1, {%3, %4}], [%2], %5, %6;\n}" ::"r"(dst),
               "l"(m), "r"(bar), "r"(c0), "r"(c1), "h"((uint16_t)3), "l"(pol)
               : "memory");
}
__device__ __forceinline__ void tma_ld3(uint32_t dst, const CUtensorMap* m, int c1, int c2, uint32_t bar, uint64_t pol) {
  asm volatile(ELECTED
               "cp.async.bulk.tensor.3d.shared::cluster.global.mbarrier::complete_tx::bytes.L2::cache_hint [%0], [%1, {%3, %4, "
               "%5}], [%2], %6;\n}" ::"r"(dst),
               "l"(m), "r"(bar), "r"(0), "r"(c1), "r"(c2), "l"(pol)
               : "memory");
}
__device__ __forceinline__ void tma_ld4(uint32_t dst, const CUtensorMap* m, int c3, uint32_t bar, uint64_t pol) {
  asm volatile(ELECTED
               "cp.async.bulk.tensor.4d.shared::cluster.global.mbarrier::complete_tx::bytes.L2::cache_hint [%0], [%1, {%3, %3, "
               "%3, %4}], [%2], %5;\n}" ::"r"(dst),
               "l"(m), "r"(bar), "r"(0), "r"(c3), "l"(pol)
               : "memory");
}
__device__ __forceinline__ void tma_st3(const CUtensorMap* m, int c1, int c2, uint32_t src, bool add) {
  if (add)
    asm volatile(ELECTED "cp.reduce.async.bulk.tensor.3d.global.shared::cta.add.bulk_group [%0, {%2, %3, %4}], [%1];\n}" ::"l"(m), "r"(src),
                 "r"(0), "r"(c1), "r"(c2)
                 : "memory");
  else
    asm volatile(ELECTED "cp.async.bulk.tensor.3d.global.shared::cta.bulk_group [%0, {%2, %3, %4}], [%1];\n}" ::"l"(m), "r"(src), "r"(0),
                 "r"(c1), "r"(c2)
                 : "memory");
}
__device__ __forceinline__ void wgmma_fence() { asm volatile("wgmma.fence.sync.aligned;" ::: "memory"); }
__device__ __forceinline__ void wgmma_commit() { asm volatile("wgmma.commit_group.sync.aligned;" ::: "memory"); }
template <int N>
__device__ __forceinline__ void wgmma_wait() {
  asm volatile("wgmma.wait_group.sync.aligned %0;" ::"n"(N) : "memory");
}
template <int N>
__device__ __forceinline__ void wgmma_wait_pin(int never, int c) {
  asm volatile("{\n.reg .pred p;\nsetp.eq.u32 p, %1, %2;\nAGAIN:\nwgmma.wait_group.sync.aligned %0;\n@p bra.uni AGAIN;\n}" ::"n"(N),
               "r"(never), "r"(c)
               : "memory");
}
__device__ __forceinline__ void pin_order(int never, int c) {
  asm volatile("{\n.reg .pred p;\nsetp.eq.u32 p, %0, %1;\nAGAIN:\n@p nanosleep.u32 1;\n@p bra.uni AGAIN;\n}" ::"r"(never), "r"(c) : "memory");
}
template <int N>
__device__ __forceinline__ void fence_regs(float (&d)[N]) {
#pragma unroll
  for (int i = 0; i < N; i++) asm volatile("" : "+f"(d[i])::"memory");
}
__device__ __forceinline__ void fence_async_smem() { asm volatile("fence.proxy.async.shared::cta;" ::: "memory"); }
__device__ __forceinline__ void bar_sync(int id, int n) { asm volatile("bar.sync %0, %1;" ::"r"(id), "r"(n) : "memory"); }
__device__ __forceinline__ void bar_arrive(int id, int n) {
  asm volatile("bar.arrive %0, %1;" ::"r"(id), "r"(n) : "memory");
}
__device__ __forceinline__ void stsm_x4_t(uint32_t addr, uint32_t r0, uint32_t r1, uint32_t r2, uint32_t r3) {
  asm volatile("stmatrix.sync.aligned.m8n8.x4.trans.shared.b16 [%0], {%1, %2, %3, %4};" ::"r"(addr), "r"(r0), "r"(r1),
               "r"(r2), "r"(r3)
               : "memory");
}
__device__ __forceinline__ void stsm_x4_t_pin(uint32_t addr, uint32_t r0, uint32_t r1, uint32_t r2, uint32_t r3, int never, int c) {
  asm volatile(
      "{\n.reg .pred p;\nsetp.eq.u32 p, %5, %6;\nAGAIN:\n"
      "stmatrix.sync.aligned.m8n8.x4.trans.shared.b16 [%0], {%1, %2, %3, %4};\n@p bra.uni AGAIN;\n}" ::"r"(addr),
      "r"(r0), "r"(r1), "r"(r2), "r"(r3), "r"(never), "r"(c)
      : "memory");
}
__device__ __forceinline__ void stsm_x2_t_pin(uint32_t addr, uint32_t r0, uint32_t r1, int never, int c) {
  asm volatile(
      "{\n.reg .pred p;\nsetp.eq.u32 p, %3, %4;\nAGAIN:\n"
      "stmatrix.sync.aligned.m8n8.x2.trans.shared.b16 [%0], {%1, %2};\n@p bra.uni AGAIN;\n}" ::"r"(addr),
      "r"(r0), "r"(r1), "r"(never), "r"(c)
      : "memory");
}
__device__ __forceinline__ uint32_t pack_bf16(float lo, float hi) {
  uint32_t r;
  asm("cvt.rn.bf16x2.f32 %0, %1, %2;" : "=r"(r) : "f"(hi), "f"(lo));
  return r;
}
__device__ __forceinline__ float ex2(float x) {
  float y;
  asm("ex2.approx.ftz.f32 %0, %1;" : "=f"(y) : "f"(x));
  return y;
}
__device__ __forceinline__ uint32_t mk_desc(uint32_t addr) { return (1u << 16) | ((addr & 0x3FFFFu) >> 4); }

template <int TA, int TB = 0, int KV = 0>
__device__ __forceinline__ void wgmma_n112(float (&d)[56], uint32_t descA, uint32_t descB, int scaleD) {
  asm volatile(
      "{\n.reg .pred p;\n.reg .b32 hi, hb;\n.reg .b64 da, db;\nsetp.ne.b32 p, %58, 0;\n"
      "mov.b32 hi, %62;\nmov.b32 hb, %61;\nmov.b64 da, {%56, hi};\nmov.b64 db, {%57, hb};\n"
      "wgmma.mma_async.sync.aligned.m64n112k16.f32.bf16.bf16 "
      "{%0, %1, %2, %3, %4, %5, %6, %7, %8, %9, %10, %11, %12, %13, "
      "%14, %15, %16, %17, %18, %19, %20, %21, %22, %23, %24, %25, %26, %27, "
      "%28, %29, %30, %31, %32, %33, %34, %35, %36, %37, %38, %39, %40, %41, "
      "%42, %43, %44, %45, %46, %47, %48, %49, %50, %51, %52, %53, %54, %55}, "
      "da, db, p, 1, 1, %59, %60;\n}\n"
      : "+f"(d[0]), "+f"(d[1]), "+f"(d[2]), "+f"(d[3]), "+f"(d[4]), "+f"(d[5]), "+f"(d[6]),
        "+f"(d[7]), "+f"(d[8]), "+f"(d[9]), "+f"(d[10]), "+f"(d[11]), "+f"(d[12]), "+f"(d[13]),
        "+f"(d[14]), "+f"(d[15]), "+f"(d[16]), "+f"(d[17]), "+f"(d[18]), "+f"(d[19]), "+f"(d[20]),
        "+f"(d[21]), "+f"(d[22]), "+f"(d[23]), "+f"(d[24]), "+f"(d[25]), "+f"(d[26]), "+f"(d[27]),
        "+f"(d[28]), "+f"(d[29]), "+f"(d[30]), "+f"(d[31]), "+f"(d[32]), "+f"(d[33]), "+f"(d[34]),
        "+f"(d[35]), "+f"(d[36]), "+f"(d[37]), "+f"(d[38]), "+f"(d[39]), "+f"(d[40]), "+f"(d[41]),
        "+f"(d[42]), "+f"(d[43]), "+f"(d[44]), "+f"(d[45]), "+f"(d[46]), "+f"(d[47]), "+f"(d[48]),
        "+f"(d[49]), "+f"(d[50]), "+f"(d[51]), "+f"(d[52]), "+f"(d[53]), "+f"(d[54]), "+f"(d[55])
      : "r"(descA), "r"(descB), "r"(scaleD), "n"(TA), "n"(TB), "n"(TB ? 8 : 0x40000040), "n"(KV ? 0x40000080 : 0x40000040));
}

template <int T>
__device__ __forceinline__ void pack_half(float (&pk)[56], const float (&a)[56]) {
#pragma unroll
  for (int i = 0; i < 28; i++) pk[28 * T + i] = __uint_as_float(pack_bf16(a[2 * i], a[2 * i + 1]));
}
template <int T>
__device__ __forceinline__ void fence_half(float (&pk)[56]) {
#pragma unroll
  for (int i = 0; i < 28; i++) asm volatile("" : "+f"(pk[28 * T + i])::"memory");
}
template <int T, int LO = 0, int HI = 7>
__device__ __forceinline__ void store_half(uint32_t addr, const float (&pk)[56]) {
#pragma unroll
  for (int q = LO; q < HI; q++) {
    const float* r = pk + 28 * T + 4 * q;
    stsm_x4_t(addr + T * PANEL + q * 2048, __float_as_uint(r[0]), __float_as_uint(r[1]), __float_as_uint(r[2]), __float_as_uint(r[3]));
  }
}

template <int T>
__device__ __forceinline__ void q_half(uint32_t addr, float (&pk)[56], const float (&a)[56], int never) {
#pragma unroll
  for (int q = 0; q < 7; q++) {
    uint32_t r[4];
#pragma unroll
    for (int i = 0; i < 4; i++) {
      r[i] = pack_bf16(a[8 * q + 2 * i] * kQScale, a[8 * q + 2 * i + 1] * kQScale);
      pk[28 * T + 4 * q + i] = __uint_as_float(r[i]);
    }
    if (q < 6 && (Q_PIN >> q & 1)) stsm_x4_t_pin(addr + T * PANEL + q * 2048, r[0], r[1], r[2], r[3], never, 32 + 2 * (7 * T + q));
    else stsm_x4_t(addr + T * PANEL + q * 2048, r[0], r[1], r[2], r[3]);
  }
}

__device__ __forceinline__ float bf_lo(uint32_t u) { return __uint_as_float(u << 16); }
__device__ __forceinline__ float bf_hi(uint32_t u) { return __uint_as_float(u & 0xFFFF0000u); }

__device__ __forceinline__ void fma8(float* o, float a, const uint4& w, float c) {
  o[0] = fmaf(a, bf_lo(w.x), o[0] * c), o[1] = fmaf(a, bf_hi(w.x), o[1] * c);
  o[2] = fmaf(a, bf_lo(w.y), o[2] * c), o[3] = fmaf(a, bf_hi(w.y), o[3] * c);
  o[4] = fmaf(a, bf_lo(w.z), o[4] * c), o[5] = fmaf(a, bf_hi(w.z), o[5] * c);
  o[6] = fmaf(a, bf_lo(w.w), o[6] * c), o[7] = fmaf(a, bf_hi(w.w), o[7] * c);
}
__device__ __forceinline__ void slow_rows(uint4* qrow, int tq, const __nv_bfloat16* xp, const __nv_bfloat16* wp,
                                          const __nv_bfloat16* kp, const __nv_bfloat16* vp, __nv_bfloat16* op) {
  if (tq >= NQ) return;
#pragma unroll 1
  for (int c = 0; c < 16; c++) {
    float q[8] = {};
#pragma unroll 1
    for (int k = 0; k < kD; k++)
      fma8(q, __bfloat162float(xp[tq * kD + k]), __ldg(reinterpret_cast<const uint4*>(wp + k * (kH * kDh)) + c), 1.f);
    qrow[c * 128] = make_uint4(pack_bf16(q[0] * kQScale, q[1] * kQScale), pack_bf16(q[2] * kQScale, q[3] * kQScale),
                               pack_bf16(q[4] * kQScale, q[5] * kQScale), pack_bf16(q[6] * kQScale, q[7] * kQScale));
  }
#pragma unroll 1
  for (int pass = 0; pass < 4; pass++) {
    float o[32] = {}, m = -INFINITY, l = 0.f;
#pragma unroll 1
    for (int key = 0; key < kSk; key++) {
      const uint4* kr = reinterpret_cast<const uint4*>(kp + key * kDh);
      const uint4* vr = reinterpret_cast<const uint4*>(vp + key * kDh) + 4 * pass;
      float s = 0.f;
#pragma unroll 1
      for (int c = 0; c < 16; c++) {
        const uint4 q = qrow[c * 128], k = __ldg(kr + c);
        s = fmaf(bf_lo(q.x), bf_lo(k.x), s); s = fmaf(bf_hi(q.x), bf_hi(k.x), s);
        s = fmaf(bf_lo(q.y), bf_lo(k.y), s); s = fmaf(bf_hi(q.y), bf_hi(k.y), s);
        s = fmaf(bf_lo(q.z), bf_lo(k.z), s); s = fmaf(bf_hi(q.z), bf_hi(k.z), s);
        s = fmaf(bf_lo(q.w), bf_lo(k.w), s); s = fmaf(bf_hi(q.w), bf_hi(k.w), s);
      }
      const float mn = fmaxf(m, s);
      const float ms = (mn == -INFINITY) ? 0.f : mn;
      const float corr = ex2(m - ms), p = ex2(s - ms);
      l = l * corr + p;
      m = mn;
      const float pb = __bfloat162float(__float2bfloat16(p));
#pragma unroll
      for (int c = 0; c < 4; c++) fma8(o + 8 * c, pb, __ldg(vr + c), corr);
    }
    const float sc = __fdividef(1.f, l);
    __nv_bfloat16* dst = op + (pass >> 1) * PANEL + (pass & 1) * 3584 + (tq >> 3) * 64 + (tq & 7);
#pragma unroll
    for (int d = 0; d < 32; d++) dst[(d >> 3) * 896 + (d & 7) * 8] = __float2bfloat16(o[d] * sc);
  }
}

__device__ __forceinline__ uint32_t launch_epoch() { return atomicAdd(&g_ticket, 1u) / gridDim.x; }

__global__ void __cluster_dims__(2, 1, 1) __launch_bounds__(384, 1) mha_fused_kernel(const __grid_constant__ Params prm) {
  extern __shared__ __align__(1024) unsigned char smem_raw[];

  const uint32_t sb = (smem_u32(smem_raw) + 1023u) & ~1023u;
  const uint32_t full0 = sb + SM_BAR, empty0 = full0 + 8 * NBAR, sfull0 = empty0 + 8 * NBAR;
  const uint32_t cred0 = sfull0 + 32, redo0 = cred0 + 64, epoch_addr = redo0 + 8, go_bar = redo0 + 16, ok_bar = redo0 + 24;
  const uint32_t rank = blockIdx.x & 1, pair = blockIdx.x >> 1;
  const uint32_t head = prm.head[pair];
  const int u_begin = head & 1023, u_end = u_begin + ((head >> 10) & 31);
  const uint32_t delay = ((head >> 15) & 255) * 256;
  const int tid = threadIdx.x;
  const int wid = __shfl_sync(0xffffffffu, tid >> 5, 0), wg = wid >> 2;

  if (wg == 2) {
    asm volatile("setmaxnreg.dec.sync.aligned.u32 %0;" ::"n"(504 - 2 * CREGS));
    const int warp = wid & 3, lane = tid & 31;
    bar_sync(0, 384);
    asm volatile("barrier.cluster.arrive.relaxed.aligned;" ::: "memory");
    if (warp < 3 && delay)
      asm volatile(
          "{\n.reg .pred p, q;\n.reg .u32 t0, t;\nmov.u32 t0, %%clock;\n"
          "SPIN:\nnanosleep.u32 100;\nmov.u32 t, %%clock;\nsub.u32 t, t, t0;\nsetp.lt.u32 p, t, %0;\n"
          "vote.sync.all.pred q, p, 0xffffffff;\n@q bra.uni SPIN;\n}" ::"r"(delay));
    auto slot_addr = [&](uint32_t i) { return sb + SM_RING + ring_slot(i) * SLOT; };
    auto full_bar = [&](uint32_t i) { return full0 + 8 * ring_slot(i); };
    const int count = (head >> 10) & 31;
    if (warp == 0) {
      uint32_t it = 6, prev = 0, code = head >> 23;
      auto acquire = [&](uint32_t i) { mbar_wait_warp(empty0 + 8 * ring_slot(i), ring_par(i) ^ 1); };
      uint32_t rblk = 0, rleft = 0;
      auto block_read = [&]() {
        asm volatile(ELECTED "red.relaxed.gpu.global.add.u32 [%0], 1;\n}" ::"l"(&g_rd[prm.blk[rblk] & 511]) : "memory");
        rblk++;
        rleft--;
      };
#pragma unroll 1
      for (int n = 1; n <= count; n++) {
        const uint32_t pat = unit_pattern(code, prev);
        const Unit u = decode_unit(code, rank);
        const int br = u.g >> 4;
        const CUtensorMap* mw = (u.attn ? prm.wq : prm.wo) + br;
        const int nslab = u.nslab;
#pragma unroll 1
        for (int k = n == 1 ? 2 : 0, pos = n == 1; k < nslab; k++) {
          const uint32_t i = it + (pos == 0);
          acquire(i);
          e_expect_tx(full_bar(i), SLOT);
          tma_ld3(slot_addr(i), mw, u.h0 * 256 + k * 64, u.hc * 2, full_bar(i), kEvictNormal);
          if (rleft && (k & 3) == 2 && k != 6) {
#pragma unroll 1
            do block_read();
            while (rleft && k == 2);
          }
          if (!u.attn && k == 4) rblk = u.g * 16 + u.h0, rleft = nslab >> 2;
          it = i + 1 + (pos == 0);
          pos = next_pos(pos, k, pat);
        }
        if (u.attn) {
          const int row0 = ((u.g & 15) * kH + u.hc) * kSk;
#pragma unroll 1
          for (int j = 0; j < kSk / 32; j++, it++) {
            acquire(it);
            e_expect_tx(full_bar(it), SLOT);
            const int isv = j == 31 || (j > 0 && !(j & 1));
            tma_ld4(slot_addr(it), &prm.kv[2 * isv + br], row0 / 8 + (((j + 1) >> 1) - isv) * 8, full_bar(it), kEvictFirst);
            if (j == kSk / 32 - 2) e_arrive(go_bar, 1);
          }
        }
        prev = code;
        code = prm.unit[u_begin + n];
      }
      if (rleft) {
        acquire(it + NSLOT - 1);
#pragma unroll 1
        while (rleft) block_read();
      }
    } else if (warp < 3) {
      asm volatile("barrier.cluster.wait.acquire.aligned;" ::: "memory");
      const int w = warp == 1 ? rank : rank ^ 1;
      uint32_t it = 6, nc = 0, pph = 0, go_ph = 0, prev = 0, code = head >> 23;
      const unsigned int* flags0 = g_cnt + (lane & 15);
      uint32_t peer_cred0;
      asm("mapa.shared::cluster.u32 %0, %1, %2;" : "=r"(peer_cred0) : "r"(cred0), "r"(rank ^ 1));
#pragma unroll 1
      for (int n = 1; n <= count; n++) {
        const uint32_t pat = unit_pattern(code, prev);
        Unit u = decode_unit(code, rank);
        const CUtensorMap* mx = u.attn ? &prm.x[u.g >> 4] : &prm.o_ld;
        const int nslab = u.nslab;
        const bool polls = !u.attn && (warp == 1 || !u.mc);
        uint32_t done = 0, ready = 0;
        if (polls) {
          asm volatile("ld.volatile.shared.u32 %0, [%1];" : "=r"(done) : "r"(epoch_addr) : "memory");
          done *= 2;
        }
        const unsigned int* flags;
        asm("add.u64 %0, %1, %2;" : "=l"(flags) : "l"(flags0), "l"((uint64_t)(uint32_t)(u.g * 64)));
        const uint64_t xpol = u.attn ? kEvictNormal : kEvictFirst;
        int xcol = n == 1 ? 128 : 0, xrow = (u.g & 15) * kSq + w * NQ;
#pragma unroll 1
        for (int k = n == 1 ? 2 : 0, pos = n == 1; k < nslab; k++) {
          if (polls && (k & 2) == 0) {
            const uint32_t hp = u.h0 + (k >> 2);
            if ((k & 1) == 0) {
              if (!(ready >> hp & 1)) ready = flags_wait(flags, done, 1u << hp);
              xrow = (prm.blk[u.g * 16 + hp] & 511) * (4 * kSq) + w * NQ;
            } else if (!(ready >> hp & 2)) {
              ready = flags_wait(flags, done, 0);
            }
          }
          const uint32_t i = it + 2 * w, q = pos - 1;
          const uint32_t fbar = full0 + 8 * (pos == 0 ? ring_slot(i) : NSLOT + 4 * w + q);
          const uint32_t dst = pos == 0 ? slot_addr(i) : sb + SM_PANEL + (4 * w + q) * PANEL;
          const uint32_t par = (pos == 0 ? ring_round(i) : pph >> q) & 1;
          pph ^= pos == 0 ? 0u : 1u << q;
          it += 1 + 2 * (pos == 0);
          pos = next_pos(pos, k, pat);
          mbar_wait_warp(fbar + 8 * NBAR, par ^ 1);
          e_expect_tx(fbar, PANEL);
          if (!u.mc) {
            tma_ld2(dst, mx, xcol, xrow, fbar, xpol);
          } else {
            if (warp == 1) {
              if (it > 10) mbar_wait_warp(cred0 + 8 * (nc & 7), (nc >> 3) & 1);
              tma_ld2_mc(dst, mx, xcol, xrow, fbar, xpol);
            } else if (it > 10) {
              asm volatile(ELECTED "mbarrier.arrive.shared::cluster.b64 _, [%0];\n}" ::"r"(peer_cred0 + 8 * (nc & 7)) : "memory");
            }
            nc += it > 10;
          }
          xcol += u.attn ? 64 : 0;
          xrow += u.attn ? 0 : kSq;
        }
        if (u.attn) {
          mbar_wait_warp(go_bar, go_ph);
          go_ph ^= 1;
          it += kSk / 32;
        }
        prev = code;
        code = prm.unit[u_begin + n];
      }
    } else {
      uint32_t epoch = 0, prev = 0;
      if (lane == 0) epoch = launch_epoch();
      epoch = __shfl_sync(0xffffffffu, epoch, 0);
      asm volatile("st.volatile.shared.u32 [%0], %1;" ::"r"(epoch_addr), "r"(epoch + 1) : "memory");
      auto publish = [&](unsigned int* p) {
        __syncwarp();
        asm volatile(ELECTED "red.release.gpu.global.add.u32 [%0], 1;\n}" ::"l"(p) : "memory");
      };
#pragma unroll 1
      for (int n = 0; n < count; n++) {
        const uint32_t code = prm.unit[u_begin + n], ph = n & 1;
        if (!(code & 0x8000u)) {
          const uint32_t blk = prm.blk[code & 511], gen = (blk >> 9) & 7;
          if (gen > 0) flag_wait(&g_rd[blk & 511], 5 * (epoch * (blk >> 12) + gen));
        }
        __syncwarp();
        e_arrive(ok_bar, 1);
        const uint32_t nx = n + 1 < count ? prm.unit[u_begin + n + 1] : 0;
        if (!(nx & 0x8000u) && (nx & 0x1800u)) {
          const Unit v = decode_unit(nx, rank);
          if (nx & 0x1000u) {
            const char* p = reinterpret_cast<const char*>(prm.xp[v.g >> 4] + ((v.g & 15) * kSq + rank * NQ) * kD) + lane * 128;
#pragma unroll 1
            for (int i = 0; i < NQ * kD * 2 / 4096; i++, p += 4096) {
              asm volatile("prefetch.global.L2 [%0];" ::"l"(p));
              __nanosleep(100);
            }
          }
          if (nx & 0x800u) {
            const char* p = reinterpret_cast<const char*>(prm.wp[v.g >> 4] + v.hc * kDh + (lane >> 1) * (kH * kDh)) + (lane & 1) * 128;
#pragma unroll 1
            for (int i = 0; i < kD / 16; i++, p += 16 * (kH * kDh * 2)) {
              asm volatile("prefetch.global.L2 [%0];" ::"l"(p));
              __nanosleep(100);
            }
          }
        }
        const bool clear = (code & 0xA000u) == 0x2000u;
        const uint32_t oc = clear ? nx : code;
        const Unit u = decode_unit(oc, rank);
        const int row = (u.g & 15) * kSq, cb = (u.g >> 4) * 10 + u.hc * 2;
        unsigned int* pc = g_pc + (oc >> 8 & 127) * 32 + rank;
        if (!(code & 0x8000u)) {
          if (clear) {
            uint4* o = reinterpret_cast<uint4*>(prm.op + (row + (lane >> 4)) * (2 * kD) + cb * 64) + (lane & 15);
#pragma unroll 1
            for (int r = 0; r < kSq / 2; r++, o += 4 * kD / 8) {
              *o = make_uint4(0, 0, 0, 0);
              __nanosleep(40);
            }
            publish(pc + 2 * (oc & 15));
          }
#pragma unroll 1
          for (int q = 0; q < 4; q++) mbar_wait_warp(sfull0 + 8 * q, ph);
          publish(&g_cnt[code & 511]);
        } else {
          const bool cleared = (prev & 0xA000u) == 0x2000u;
          if (u.h0) flag_wait(pc + 2 * (u.h0 - 1), epoch + 1);
          asm volatile("fence.proxy.async.global;" ::: "memory");
#pragma unroll 1
          for (int q = 0; q < 4; q++) {
            const int w = n + 1 < count ? q & 1 : q >> 1, t = n + 1 < count ? q >> 1 : q & 1;
            mbar_wait_warp(sfull0 + 8 * (2 * t + w), ph);
            fence_async_smem();
#pragma unroll 1
            for (int r = 0; r < NQ; r += ST_ROWS) {
              tma_st3(&prm.out, row + w * NQ + r, cb + t, sb + SM_PANEL + (4 * w + 2 + t) * PANEL + r * 128, u.h0 || cleared);
              asm volatile("cp.async.bulk.commit_group;" ::: "memory");
              if (n + 1 < count) asm volatile("cp.async.bulk.wait_group.read 0;" ::: "memory");
            }
            __syncwarp();
            e_arrive(empty0 + 8 * (NSLOT + 4 * w + 2 + t), 2);
          }
          if ((code & 15) != 15 && !cleared) {
            asm volatile("cp.async.bulk.wait_group 0;" ::: "memory");
            asm volatile("fence.proxy.async.global;" ::: "memory");
            publish(pc + 2 * (code & 15));
          }
        }
        prev = code;
      }
      asm volatile("cp.async.bulk.wait_group 0;" ::: "memory");
    }
  } else {
    const int tq = tid & 127, lane = tid & 31, warp = tq >> 5;
    if (tid == 0) {
#pragma unroll
      for (int i = 0; i < NBAR; i++) {
        mbar_init(full0 + 8 * i, 1);
        mbar_init(empty0 + 8 * i, 2);
      }
#pragma unroll
      for (int i = 0; i < 12; i++) mbar_init(sfull0 + 8 * i, i < 4 ? 4 : 1);
      mbar_init(go_bar, 1);
      mbar_init(ok_bar, 1);
      asm volatile("st.shared.v4.u32 [%0], {%1, %1, %1, %1};" ::"r"(redo0), "r"(0) : "memory");
      asm volatile("fence.mbarrier_init.release.cluster;" ::: "memory");
      fence_async_smem();
    }
    if (wid == 0) {
      __syncwarp();
      const Unit u = decode_unit(head >> 23, rank);
#pragma unroll
      for (int i = 0; i < 6; i++) {
        e_expect_tx(full0 + 8 * i, i % 3 == 1 ? SLOT : PANEL);
        if (i % 3 == 1) tma_ld3(sb + SM_RING + i * SLOT, &prm.wq[u.g >> 4], i / 3 * 64, u.hc * 2, full0 + 8 * i, kEvictNormal);
        else tma_ld2(sb + SM_RING + i * SLOT, &prm.x[u.g >> 4], i / 3 * 64, (u.g & 15) * kSq + i % 3 / 2 * NQ, full0 + 8 * i, kEvictNormal);
      }
    } else if (wid < 5) {
      asm volatile(ELECTED "prefetch.tensormap [%0];\n}" ::"l"(prm.x + 2 * (wid - 1) + (head >> 31)) : "memory");
    }
    bar_sync(0, 384);
    asm volatile("barrier.cluster.arrive.relaxed.aligned;" ::: "memory");
    asm volatile("setmaxnreg.inc.sync.aligned.u32 %0;" ::"n"(CREGS));
    const uint32_t stage = sb + SM_PANEL + wg * 4 * PANEL;
    const uint32_t st_q = __shfl_sync(
        0xffffffffu, stage + ((lane >> 4) * 8 + (lane & 7)) * 128 + (((2 * warp + ((lane >> 3) & 1)) ^ (lane & 7)) << 4), lane);
    const uint32_t st_p = st_q + 2 * PANEL;
    const uint32_t dq = mk_desc(stage), dring = mk_desc(sb + SM_RING);
    float acc[2][56], s[56] = {};
    const int never = (sb >> 24) & ~1u;
    uint32_t it = 0, pph = 0;
    auto wait_full = [&](uint32_t i) { mbar_wait_warp(full0 + 8 * ring_slot(i), ring_par(i)); };
    auto test = [&](uint32_t bar, uint32_t par) { return mbar_test_if(bar, par, warp == 0); };
    auto probe = [&](uint32_t i) { return test(full0 + 8 * ring_slot(i), ring_par(i)); };
    auto release = [&](uint32_t i) { mbar_arrive1_if(empty0 + 8 * ring_slot(i), tq == 0); };
    auto slot_desc = [&](uint32_t i) { return dring + ring_slot(i) * (SLOT >> 4); };
    if (wg == 1) bar_arrive(1, 256);

    struct Fin {
      uint32_t rp[16];
      char* dst;
    };
    uint32_t ps[14] = {};
    float l[28] = {};
    auto step_sums = [&]() {
#pragma unroll
      for (int g = 0; g < 14; g++) asm("add.rn.bf16x2 %0, %0, %1;" : "+r"(ps[g]) : "r"(pack_bf16(l[2 * g], l[2 * g + 1])));
#pragma unroll
      for (int q = 0; q < 3; q++) stsm_x4_t(st_p + q * 2048, ps[2 * q], ps[2 * q + 7], ps[2 * q + 1], ps[2 * q + 8]);
      asm volatile("stmatrix.sync.aligned.m8n8.x2.trans.shared.b16 [%0], {%1, %2};" ::"r"(st_p + 3 * 2048), "r"(ps[6]), "r"(ps[13])
                   : "memory");
    };
    auto flag_bad = [&](bool bad) {
      asm volatile("{\n.reg .pred p;\nsetp.ne.u32 p, %1, 0;\n@p st.shared.u32 [%0], %1;\n}" ::"r"(redo0 + 4 * wg), "r"((uint32_t)bad)
                   : "memory");
    };
    auto step_finite = [&](bool live) {
      uint32_t z[4] = {0, 0, 0, 0};
#pragma unroll
      for (int i = 0; i < 28; i++)
        asm volatile("fma.rn.bf16x2 %0, %1, %2, %0;" : "+r"(z[i & 3]) : "r"(__float_as_uint(s[2 * i])), "r"(__float_as_uint(s[2 * i + 1])));
      asm volatile("add.rn.bf16x2 %0, %0, %1;" : "+r"(z[0]) : "r"(z[1]));
      asm volatile("add.rn.bf16x2 %0, %0, %1;" : "+r"(z[2]) : "r"(z[3]));
      asm volatile("add.rn.bf16x2 %0, %0, %1;" : "+r"(z[0]) : "r"(z[2]));
      flag_bad(live && (((z[0] & 0x7F807F80u) + 0x00800080u) & 0x80008000u));
    };
    auto rows_addr = [&]() {
      const uint32_t q = min(tq, NQ - 1), hi = q >= 56, n = q - 56 * hi;
      return stage + 2 * PANEL + n * 128 + ((hi ^ (n & 7)) << 4);
    };
    auto rows_load = [&](Fin& f, uint32_t a) {
#pragma unroll
      for (int c = 0; c < 4; c++)
        asm volatile("ld.shared.v4.u32 {%0, %1, %2, %3}, [%4];"
                     : "=r"(f.rp[4 * c]), "=r"(f.rp[4 * c + 1]), "=r"(f.rp[4 * c + 2]), "=r"(f.rp[4 * c + 3])
                     : "r"(a ^ (c << 5))
                     : "memory");
    };
    auto step_rows = [&](const Fin& f, bool live) {
      const uint32_t q = min(tq, NQ - 1);
      float t = 0.f, t2 = 0.f;
#pragma unroll
      for (int i = 0; i < 8; i++) {
        uint32_t v;
        asm("add.rn.bf16x2 %0, %1, %2;" : "=r"(v) : "r"(f.rp[2 * i]), "r"(f.rp[2 * i + 1]));
        t += bf_lo(v), t2 += bf_hi(v);
      }
      t += t2;
      float r;
      asm("rcp.approx.ftz.f32 %0, %1;" : "=f"(r) : "f"(t));
      asm volatile("st.shared.u16 [%0], %1;" ::"r"(sb + SM_RCP + wg * 320 + (q >> 1 & 3) * 80 + (q >> 3) * 4 + (q & 1) * 2),
                   "h"((uint16_t)pack_bf16(r, r))
                   : "memory");
      flag_bad(live && !(t >= 9.094947017729282e-13f && t <= 1.329227995784916e36f));
    };
    auto step_scales = [&](Fin& f) {
#pragma unroll
      for (int c = 0; c < 4; c++)
        asm volatile("ld.shared.v4.u32 {%0, %1, %2, %3}, [%4];"
                     : "=r"(f.rp[4 * c]), "=r"(f.rp[4 * c + 1]), "=r"(f.rp[4 * c + 2]), "=r"(f.rp[4 * c + 3])
                     : "r"(sb + SM_RCP + wg * 320 + (lane & 3) * 80 + c * 16)
                     : "memory");
    };
    auto o_base = [&](uint32_t u) {
      return reinterpret_cast<char*>(g_o) + (size_t)((((prm.blk[u & 511] & 511u) * 4 + rank * 2) * 2 + wg) * (uint32_t)PANEL);
    };
    auto step_write = [&](const Fin& f, int lo, int hi) {
#pragma unroll
      for (int i = lo; i < hi; i++) {
        uint32_t v = __float_as_uint(s[i]);
        asm("mul.rn.bf16x2 %0, %0, %1;" : "+r"(v) : "r"(f.rp[(i % 28) >> 1]));
        s[i] = __uint_as_float(v);
        asm volatile("st.global.u32 [%0], %1;" ::"l"(f.dst + (i / 28) * 2 * PANEL + (i & 1) * 1792 + ((i % 28) >> 1) * 128), "r"(v) : "memory");
      }
    };
    auto keep_alive = [&](int lo, int hi, int c) {
      if (never == c) {
#pragma unroll
        for (int i = lo; i < hi; i++) asm volatile("st.shared.f32 [%0], %1;" ::"r"(stage + 4 * i), "f"(s[i]) : "memory");
        pin_order(never, c);
      }
    };
    auto step_signal = [&](int t) {
      __syncwarp();
      mbar_arrive1_if(sfull0 + 8 * (2 * t + wg), lane == 0);
    };
    auto free_panel = [&](int q) { mbar_arrive1_if(empty0 + 8 * (NSLOT + 4 * wg + q), tq < 2); };
    auto read_verdict = [&]() {
      uint32_t redo;
      asm volatile("ld.shared.u32 %0, [%1];" : "=r"(redo) : "r"(redo0 + 4 * wg) : "memory");
      return redo;
    };
    auto step_redo = [&](uint32_t prev) {
      asm volatile("" : "+r"(prev));
      bar_sync(3 + wg, 128);
      if (tq == 0) asm volatile("st.shared.u32 [%0], %1;" ::"r"(redo0 + 4 * wg), "r"(0) : "memory");
      const Unit u = decode_unit(prev & 511, rank);
      const int br = u.g >> 4, b = u.g & 15;
      const size_t off = (size_t)(b * kH + u.hc) * kSk * kDh;
      slow_rows(g_qrow + (blockIdx.x * 2 + wg) * (16 * 128) + tq, tq, prm.xp[br] + (b * kSq + wg * NQ) * kD, prm.wp[br] + u.hc * kDh,
                prm.kp[br] + off, prm.vp[br] + off, reinterpret_cast<__nv_bfloat16*>(o_base(prev)));
#pragma unroll
      for (int i = 0; i < 56; i++) s[i] = 0.f;
    };
    auto issue_slab = [&](uint32_t da, uint32_t db, int accum, auto split, auto tb) {
      constexpr int TB = tb.value, KS = TB ? 224 : 2;
      if (TB) db += 111 << 16;
      if (split.value == 1) {
#pragma unroll
        for (int t = 0; t < 2; t++) {
#pragma unroll
          for (int kk = 0; kk < 4; kk++) {
            if (t == 1 && kk == 2) bar_arrive(2 - wg, 256);
            wgmma_n112<1, 0, 1>(acc[t], da + t * 64 + kk * 256, db + kk * KS, 1);
          }
          wgmma_commit();
        }
      } else {
#pragma unroll
        for (int kk = 0; kk < 4; kk++) {
          if (kk == 3) bar_arrive(2 - wg, 256);
          wgmma_n112<1, TB>(acc[0], da + kk * 128, db + kk * KS, kk > 0 ? 1 : accum);
          wgmma_n112<1, TB>(acc[1], da + 512 + kk * 128, db + kk * KS, kk > 0 ? 1 : accum);
        }
        wgmma_commit();
      }
    };

    uint32_t code = head >> 23, prev = 0, pend = 0, uph = 0;
    uint32_t da = slot_desc(1), db = slot_desc(2 * wg);
    auto next_unit = [&](bool block) {
      da = slot_desc(it + 1), db = slot_desc(it + 2 * wg);
      if (block) {
        if (!__all_sync(0xffffffffu, probe(it + 1) & probe(it + 2 * wg))) {
          wait_full(it + 1);
          wait_full(it + 2 * wg);
        }
      }
    };
    wait_full(1);
    wait_full(2 * wg);
    for (int left = (head >> 10) & 31; left > 0; left--) {
      const int ui = u_end - left;
      uint32_t nxt;
      bool defer;
      auto peek = [&]() {
        const uint32_t cur = prm.unit[ui];
        nxt = __shfl_sync(0xffffffffu, (uint32_t)prm.unit[ui + 1], 0);
        defer = left > 1 && (!(nxt & 0x8000u) || ((cur & 0x8000u) ? unit_slabs(nxt) >= 10 : cur & 0x4000u));
      };
      const bool out = code & 0x8000u;
      uint32_t rel = 0;
      auto retire = [&]() {
        wgmma_wait<0>();
        fence_regs(acc[0]);
        fence_regs(acc[1]);
        mbar_arrive1_if(rel, rel);
        rel = 0;
      };
      auto turn = [&](int accum, auto mode, auto tb, auto first) {
        bar_sync(1 + wg, 256);
        if (!first.value) retire();
        wgmma_fence();
        issue_slab(da, db, accum, mode, tb);
      };
      auto take_turn = [&](int accum, auto mode, auto first) {
        if (out) turn(accum, mode, IntC<1>{}, first);
        else turn(accum, mode, IntC<0>{}, first);
      };
      Fin f;
      take_turn(0, IntC<0>{}, BoolC<true>{});
      int k = 0;
      const bool staged = pend == 2;
      if (out ? pend == 1 : !staged) {
        uint32_t redo = 0;
        static_for<0, 8>([&](auto kc) {
          constexpr int k = kc.value;
          if (k > 0) take_turn(1, IntC<0>{}, BoolC<false>{});
          if (k >= 4) keep_alive(w_cut(k - 4), w_cut(k - 3), 62 + 2 * k);
          if (k == 2) step_scales(f);
          constexpr int p0 = x_pos(0, k), p1 = x_pos(0, k + 1), o0 = x_off(0, k), o1 = x_off(0, k + 1);
          const uint32_t rw = empty0 + 8 * ring_slot(it + o0 + (p0 == 0));
          const uint32_t rx = empty0 + 8 * (p0 == 0 ? ring_slot(it + o0 + 2 * wg) : NSLOT + 4 * wg + p0 - 1);
          const uint32_t wi = it + o1 + (p1 == 0), xi = it + o1 + 2 * wg;
          const uint32_t xbar = full0 + 8 * (p1 == 0 ? ring_slot(xi) : NSLOT + 4 * wg + p1 - 1);
          const uint32_t xpar = (p1 == 0 ? ring_round(xi) : pph >> (p1 == 0 ? 0 : p1 - 1)) & 1;
          if constexpr (p1 != 0) pph ^= 1u << (p1 - 1);
          uint32_t okp = probe(wi) & test(xbar, xpar);
          if (k == 2) okp &= test(ok_bar, uph ^ pend);
          rel = pick(tq == 0, rw, pick(tq < 3 && (k < 6 || out), rx, 0));
          if (k == 0) {
            uint32_t a = rows_addr();
            asm volatile("" : "+r"(a), "+r"(okp), "+r"(rel));
            if (pend) step_sums();
            bar_sync(3 + wg, 128);
            rows_load(f, a);
          }
          if (k == 1) {
            mbar_arrive1_if(empty0 + 8 * (NSLOT + 4 * wg + 2), tq < 2 && pend);
            step_rows(f, pend);
          }
          if (k == 2) {
            step_finite(pend);
            f.dst = o_base(prev) + warp * 3584 + lane * 4;
          }
          if (k == 6) redo = read_verdict();
          if (k >= 3 && pend) step_write(f, w_cut(k - 3), w_cut(k - 2));
          if (k == 7) {
            if (__any_sync(0xffffffffu, redo)) step_redo(prev);
            __syncwarp();
            mbar_arrive1_if(sfull0 + 8 * (2 * lane + wg), lane < 2 && pend);
          }
          const bool ok = __all_sync(0xffffffffu, okp);
          da = slot_desc(wi);
          db = p1 == 0 ? slot_desc(xi) : dq + (p1 - 1) * (PANEL >> 4);
          if (!ok) {
            retire();
            wait_full(wi);
            mbar_wait_warp(xbar, xpar);
            if (k == 2) mbar_wait_warp(ok_bar, uph ^ pend);
          }
        });
        k = 8;
        if (out) turn(1, IntC<0>{}, IntC<1>{}, BoolC<false>{});
      }
      const int nslab = unit_slabs(code);
      uint32_t pos = k ? 3 : 0, wi = it + (k ? 12 : 1), xbar = full0 + 8 * (k ? NSLOT + 4 * wg + 2 : ring_slot(it + 2 * wg));
      const int kend = nslab - 2;
      if (k < kend) {
        uint32_t r = it + (k ? 13 : 3);
        const uint32_t pat = staged ? kPat1 : kPat0;
        const uint32_t keep_pos = out ? 3 : 1;
        const int keep_k = out ? nslab - 4 : 5;
#pragma unroll 1
        while (true) {
          rel = pick(tq == 0, empty0 + 8 * ring_slot(wi), pick(tq < 3 && (pos < keep_pos || k < keep_k), xbar + 8 * NBAR, 0));
          pos = next_pos(pos, k, pat);
          const bool ring = pos == 0;
          const uint32_t i = r + 2 * wg, q = pos - 1;
          wi = ring ? r + 1 : r;
          xbar = full0 + 8 * (ring ? ring_slot(i) : NSLOT + 4 * wg + q);
          const uint32_t xpar = (ring ? ring_round(i) : pph >> q) & 1;
          da = slot_desc(wi);
          db = ring ? slot_desc(i) : dq + q * (PANEL >> 4);
          pph ^= ring ? 0u : 1u << q;
          r += ring ? 3 : 1;
          const bool ok = __all_sync(0xffffffffu, probe(wi) & test(xbar, xpar));
          if (staged && k < 2) {
            if (k == 0) {
              store_half<1, 0, 4>(st_p, s);
            } else {
              store_half<1, 4, 7>(st_p, s);
              step_signal(1);
            }
          }
          if (!ok) {
            retire();
            wait_full(wi);
            mbar_wait_warp(xbar, xpar);
          }
          if (++k == kend) break;
          take_turn(1, IntC<0>{}, BoolC<false>{});
        }
      }
      it += nslab + (staged ? 8 : 4);
      const uint32_t ql = out ? 1 : 3, xl = full0 + 8 * (NSLOT + 4 * wg + ql), pl = pph >> ql & 1, dl = slot_desc(it - 1);
      pph ^= 1u << ql;
      if (!__all_sync(0xffffffffu, probe(it - 1) & test(xl, pl))) {
        retire();
        wait_full(it - 1);
        mbar_wait_warp(xl, pl);
      }
      auto last_turn = [&](auto tb) {
        constexpr int TB = tb.value;
        bar_sync(1 + wg, 256);
        retire();
        wgmma_fence();
#pragma unroll
        for (int t = 0; t < 2; t++) {
#pragma unroll
          for (int kk = 0; kk < 8; kk++)
            wgmma_n112<1, TB>(acc[t], (kk < 4 ? da : dl) + t * 512 + (kk & 3) * 128,
                              db + t * never + (TB ? 111 << 16 : 0) + (kk >> 2) * (PANEL >> 4) + (kk & 3) * (TB ? 224 : 2), 1);
          wgmma_commit();
        }
        bar_arrive(2 - wg, 256);
      };
      const uint32_t rw2 = empty0 + 8 * pick(tq == 0, ring_slot(it - 2), ring_slot(it - 1));
      if (!out) {
        {
          last_turn(IntC<0>{});
          keep_alive(28, 56, 80);
          const bool ok = __all_sync(0xffffffffu, probe(it));
          rel = pick(tq < 2, rw2, 0);
          da = slot_desc(it);
          wgmma_wait<1>();
          fence_regs(acc[0]);
          q_half<0>(st_q, s, acc[0], never);
          wgmma_wait<0>();
          fence_regs(acc[1]);
          q_half<1>(st_q, s, acc[1], never);
          mbar_arrive1_if(rel, rel);
          if (!ok) wait_full(it);
        }
        fence_async_smem();
        auto issue_s = [&](uint32_t dk, int accum) {
          wgmma_fence();
#pragma unroll
          for (int kk = 0; kk < 8; kk++)
            wgmma_n112<0, 0, 1>(s, dk + (kk >> 2) * 64 + (kk & 3) * 2, dq + (kk >> 2) * (PANEL >> 4) + (kk & 3) * 2, kk > 0 ? 1 : accum);
          wgmma_commit();
        };
        auto add_sums = [&]() {
#pragma unroll
          for (int jj = 0; jj < 14; jj++)
            asm volatile("{\n.reg .b32 t;\nshl.b32 t, %2, 16;\nadd.f32 %0, %0, t;\nand.b32 t, %2, 0xffff0000;\nadd.f32 %1, %1, t;\n}"
                         : "+f"(l[2 * jj]), "+f"(l[2 * jj + 1])
                         : "r"(ps[jj]));
        };
        auto softmax = [&](uint32_t par, int pin0) {
          const uint32_t pa = st_p + par * PANEL;
#pragma unroll
          for (int i = 0; i < 4 + SM_OFF; i++) s[i] = ex2(s[i]);
#pragma unroll
          for (int jj = 0; jj < 14; jj++) {
#pragma unroll
            for (int i = 4 * jj + 4 + SM_OFF; i < 4 * jj + 8 + SM_OFF; i++)
              if (i < 56) s[i] = ex2(s[i]);
            const uint32_t p0 = pack_bf16(s[4 * jj], s[4 * jj + 1]), p1 = pack_bf16(s[4 * jj + 2], s[4 * jj + 3]);
            stsm_x2_t_pin(pa + jj * 1024, p0, p1, never, pin0);
            s[4 * jj] = __uint_as_float(p0), s[4 * jj + 1] = __uint_as_float(p1);
            asm("add.rn.bf16x2 %0, %1, %2;" : "=r"(ps[jj]) : "r"(p0), "r"(p1));
          }
        };
        bar_sync(1 + wg, 256);
        issue_s(da, never);
        bar_arrive(2 - wg, 256);
        {
#pragma unroll
          for (int i = 0; i < 28; i++) asm volatile("mov.b32 %0, 0;" : "=f"(l[i]));
          peek();
          const bool ok = __all_sync(0xffffffffu, probe(it + 1));
          da = slot_desc(it + 1);
          wgmma_wait_pin<0>(never, 180);
          fence_regs(s);
          release(it);
          softmax(0, 176);
          if (!ok) wait_full(it + 1);
        }
        it += 1;
#pragma unroll 1
        for (int j = 1; j < 16; j++) {
          fence_async_smem();
          bar_sync(1 + wg, 256);
          issue_s(da, 0);
          pin_order(never, 2 * j + 128);
          const uint32_t okv = mbar_test(full0 + 8 * ring_slot(it + 1), ring_par(it + 1));
          const uint32_t okk = probe(it + 2);
          da = slot_desc(it + 2);
          add_sums();
          const bool ok = __all_sync(0xffffffffu, okk);
          if (!__all_sync(0xffffffffu, okv)) wait_full(it + 1);
          {
            const uint32_t dv = slot_desc(it + 1), dp = dq + (3 - (j & 1)) * (PANEL >> 4);
            wgmma_fence();
#pragma unroll
            for (int kk = 0; kk < 4; kk++) {
              wgmma_n112<1, 0, 1>(acc[0], dv + kk * 256, dp + kk * 2, kk > 0 ? 1 : j > 1);
              wgmma_n112<1, 0, 1>(acc[1], dv + 64 + kk * 256, dp + kk * 2, kk > 0 ? 1 : j > 1);
            }
          }
          wgmma_commit();
          bar_arrive(2 - wg, 256);
          wgmma_wait<1>();
          fence_regs(s);
          release(it);
          softmax(j & 1, 2 * j + 192);
          wgmma_wait<0>();
          fence_regs(acc[0]);
          fence_regs(acc[1]);
          release(it + 1);
          it += 2;
          if (!ok) {
            wait_full(it);
          }
        }
        it += 1;
        fence_async_smem();
        bar_sync(1 + wg, 256);
        wgmma_fence();
        issue_slab(da, dq + 3 * (PANEL >> 4), 1, IntC<1>{}, IntC<0>{});
        pin_order(never, 182);
        mbar_arrive1_if(empty0 + 8 * (NSLOT + 4 * wg + (tq >> 1)), tq < 4);
        rel = pick(tq == 0, empty0 + 8 * ring_slot(it - 1), pick(tq < 3, empty0 + 8 * (NSLOT + 4 * wg + 3), 0));
        next_unit(defer);
        if (defer) {
          wgmma_wait<1>();
          fence_regs(acc[0]);
          pack_half<0>(s, acc[0]);
          fence_half<0>(s);
          wgmma_wait_pin<0>(never, 172);
          fence_regs(acc[1]);
          mbar_arrive1_if(rel, rel);
          pack_half<1>(s, acc[1]);
        }
        pend = 1;
      } else {
        last_turn(IntC<1>{});
        pin_order(never, 186);
        peek();
#pragma unroll
        for (int i = 0; i < 28; i++) ps[i >> 1] = 0, l[i] = 0.f;
        mbar_wait_warp(ok_bar, uph);
        next_unit(defer);
        rel = pick(tq < 2, rw2, pick(tq < 6, empty0 + 8 * (NSLOT + 4 * wg - 1 + (tq >> 1)), 0));
        wgmma_wait<1>();
        fence_regs(acc[0]);
        pack_half<0>(s, acc[0]);
        store_half<0>(st_p, s);
        step_signal(0);
        wgmma_wait<0>();
        fence_regs(acc[1]);
        mbar_arrive1_if(rel, rel);
        pack_half<1>(s, acc[1]);
        pend = 2;
      }
      if (!defer) {
        if (pend == 2) {
          store_half<1>(st_p, s);
        } else {
          step_sums();
          bar_sync(3 + wg, 128);
          rows_load(f, rows_addr());
          f.dst = o_base(code) + warp * 3584 + lane * 4;
          mbar_wait_warp(ok_bar, uph);
          step_rows(f, true);
          bar_sync(3 + wg, 128);
          step_scales(f);
          free_panel(2);
          retire();
          pack_half<0>(s, acc[0]);
          pack_half<1>(s, acc[1]);
          step_finite(true);
          step_write(f, 0, 28);
          bar_sync(3 + wg, 128);
          const uint32_t redo = read_verdict();
          step_write(f, 28, 56);
          if (__any_sync(0xffffffffu, redo)) step_redo(code);
          step_signal(0);
        }
        step_signal(1);
        pend = 0;
#pragma unroll
        for (int i = 0; i < 28; i++) ps[i >> 1] = 0, l[i] = 0.f;
        if (left > 1) {
          wait_full(it + 1);
          wait_full(it + 2 * wg);
        }
      }
      prev = code, code = nxt, uph ^= 1;
    }
    if (wg == 0) bar_sync(1, 256);
  }
}

typedef CUresult (*EncodeFn)(CUtensorMap*, CUtensorMapDataType, cuuint32_t, void*, const cuuint64_t*, const cuuint64_t*,
                             const cuuint32_t*, const cuuint32_t*, CUtensorMapInterleave, CUtensorMapSwizzle,
                             CUtensorMapL2promotion, CUtensorMapFloatOOBfill);

bool encode(EncodeFn fn, CUtensorMap* m, const void* ptr, int rank, const cuuint64_t* dims, const cuuint64_t* strides,
            const cuuint32_t* box, CUtensorMapL2promotion promo, CUtensorMapSwizzle swz = CU_TENSOR_MAP_SWIZZLE_128B) {
  const cuuint32_t es[4] = {1, 1, 1, 1};
  return fn(m, CU_TENSOR_MAP_DATA_TYPE_BFLOAT16, rank, const_cast<void*>(ptr), dims, strides, box, es,
            CU_TENSOR_MAP_INTERLEAVE_NONE, swz, promo,
            CU_TENSOR_MAP_FLOAT_OOB_FILL_NONE) == CUDA_SUCCESS;
}
bool encode_panels(EncodeFn fn, CUtensorMap* m, const void* ptr, uint64_t rows, uint64_t cols, uint32_t box_rows,
                   uint32_t box_blocks = 2) {
  const cuuint64_t dims[3] = {64, rows, cols / 64};
  const cuuint64_t strides[2] = {cols * 2, 128};
  const cuuint32_t box[3] = {64, box_rows, box_blocks};
  CUtensorMapL2promotion promo = CU_TENSOR_MAP_L2_PROMOTION_L2_128B;
  return encode(fn, m, ptr, 3, dims, strides, box, promo);
}
bool encode_kv(EncodeFn fn, CUtensorMap* m, const void* ptr) {
  const cuuint64_t dims[4] = {64, 8, 2, (uint64_t)kB * kH * kSk / 8};
  const cuuint64_t strides[3] = {kDh * 2, 128, 8 * kDh * 2};
  const cuuint32_t box[4] = {64, 8, 2, 8};
  CUtensorMapL2promotion promo = CU_TENSOR_MAP_L2_PROMOTION_L2_128B;
  return encode(fn, m, ptr, 4, dims, strides, box, promo);
}
bool encode_2d(EncodeFn fn, CUtensorMap* m, const void* ptr, uint64_t rows, uint64_t cols, uint32_t box_rows,
               CUtensorMapSwizzle swz = CU_TENSOR_MAP_SWIZZLE_128B) {
  const cuuint64_t dims[2] = {cols, rows};
  const cuuint64_t strides[1] = {cols * 2};
  const cuuint32_t box[2] = {64, box_rows};
  CUtensorMapL2promotion promo = CU_TENSOR_MAP_L2_PROMOTION_L2_128B;
  return encode(fn, m, ptr, 2, dims, strides, box, promo, swz);
}

constexpr int kTunedPairs = 66;
const uint16_t kTunedBlock[kAttnUnits] = {
    20480, 20486, 20492, 20498, 20504, 20510, 20516, 20522, 20528, 20534, 16444, 16450, 16456, 16462, 20996, 21002,
    20481, 20487, 20493, 20499, 20505, 20511, 20517, 20523, 20529, 20535, 16445, 16451, 16457, 16463, 20997, 21003,
    20482, 20488, 20494, 20500, 20506, 20512, 20518, 20524, 20530, 20536, 16446, 16452, 16458, 20992, 20998, 21004,
    20483, 20489, 20495, 20501, 20507, 20513, 20519, 20525, 20531, 20537, 16447, 16453, 16459, 20993, 20999, 21005,
    20484, 20490, 20496, 20502, 20508, 20514, 20520, 20526, 20532, 20538, 16448, 16454, 16460, 20994, 21000, 21006,
    20485, 20491, 20497, 20503, 20509, 20515, 20521, 20527, 20533, 20539, 16449, 16455, 16461, 20995, 21001, 21007,
    21008, 21012, 21016, 21020, 21024, 21028, 21032, 21036, 21040, 21044, 21048, 16956, 16960, 16964, 16968, 16972,
    21009, 21013, 21017, 21021, 21025, 21029, 21033, 21037, 21041, 21045, 21049, 16957, 16961, 16965, 16969, 16973,
    21010, 21014, 21018, 21022, 21026, 21030, 21034, 21038, 21042, 21046, 21050, 16958, 16962, 16966, 16970, 16974,
    21011, 21015, 21019, 21023, 21027, 21031, 21035, 21039, 21043, 21047, 21051, 16959, 16963, 16967, 16971, 16975,
    21504, 21506, 21508, 21510, 21512, 21514, 21516, 21518, 21520, 21522, 21524, 21526, 21528, 21530, 21532, 21534,
    21505, 21507, 21509, 21511, 21513, 21515, 21517, 21519, 21521, 21523, 21525, 21527, 21529, 21531, 21533, 21535,
    21536, 21540, 21544, 21548, 21552, 21556, 21560, 17468, 17472, 17476, 17480, 17484, 22016, 22020, 22024, 22028,
    21537, 21541, 21545, 21549, 21553, 21557, 21561, 17469, 17473, 17477, 17481, 17485, 22017, 22021, 22025, 22029,
    21538, 21542, 21546, 21550, 21554, 21558, 21562, 17470, 17474, 17478, 17482, 17486, 22018, 22022, 22026, 22030,
    21539, 21543, 21547, 21551, 21555, 21559, 21563, 17471, 17475, 17479, 17483, 17487, 22019, 22023, 22027, 22031,
    22032, 22034, 22036, 22038, 22040, 22042, 22044, 22046, 22048, 22050, 22052, 22054, 22056, 22058, 22060, 22062,
    22033, 22035, 22037, 22039, 22041, 22043, 22045, 22047, 22049, 22051, 22053, 22055, 22057, 22059, 22061, 22063,
    22064, 22066, 22068, 22070, 22072, 22074, 17980, 17982, 17984, 17986, 17988, 17990, 17992, 17994, 17996, 17998,
    22065, 22067, 22069, 22071, 22073, 22075, 17981, 17983, 17985, 17987, 17989, 17991, 17993, 17995, 17997, 17999,
    22528, 22529, 22530, 22531, 22532, 22533, 22534, 22535, 22536, 22537, 22538, 22539, 22540, 22541, 22542, 22543,
    22544, 22545, 22546, 22547, 22548, 22549, 22550, 22551, 22552, 22553, 22554, 22555, 22556, 22557, 22558, 22559,
    22560, 22570, 22580, 4178, 4188, 4198, 4208, 4218, 4228, 4238, 4248, 4258, 4268, 4278, 4288, 4298,
    22561, 22571, 22581, 4179, 4189, 4199, 4209, 4219, 4229, 4239, 4249, 4259, 4269, 4279, 4289, 4299,
    22562, 22572, 22582, 4180, 4190, 4200, 4210, 4220, 4230, 4240, 4250, 4260, 4270, 4280, 4290, 4300,
    22563, 22573, 22583, 4181, 4191, 4201, 4211, 4221, 4231, 4241, 4251, 4261, 4271, 4281, 4291, 4301,
    22564, 22574, 22584, 4182, 4192, 4202, 4212, 4222, 4232, 4242, 4252, 4262, 4272, 4282, 4292, 4302,
    22565, 22575, 22585, 4183, 4193, 4203, 4213, 4223, 4233, 4243, 4253, 4263, 4273, 4283, 4293, 4303,
    22566, 22576, 22586, 4184, 4194, 4204, 4214, 4224, 4234, 4244, 4254, 4264, 4274, 4284, 4294, 4304,
    22567, 22577, 22587, 4185, 4195, 4205, 4215, 4225, 4235, 4245, 4255, 4265, 4275, 4285, 4295, 4305,
    22568, 22578, 4176, 4186, 4196, 4206, 4216, 4226, 4236, 4246, 4256, 4266, 4276, 4286, 4296, 4306,
    22569, 22579, 4177, 4187, 4197, 4207, 4217, 4227, 4237, 4247, 4257, 4267, 4277, 4287, 4297, 4307};
const uint8_t kTunedLen[kTunedPairs] = {
    10, 10, 10, 10, 10, 10, 10, 9, 9, 11, 9, 11, 10, 10, 10, 10, 8, 9, 11, 8, 9, 10, 10, 11, 9, 9, 10, 10, 11, 10, 10, 11, 9,
    9, 10, 9, 9, 11, 10, 10, 9, 10, 11, 10, 10, 10, 10, 10, 9, 11, 10, 10, 10, 9, 10, 10, 10, 9, 10, 11, 10, 9, 10, 10, 9, 10};
const uint8_t kTunedDelay[kTunedPairs] = {
    0, 0, 0, 0, 0, 29, 5, 0, 105, 1, 0, 0, 1, 0, 1, 0, 0, 0, 0, 109, 109, 29,
    0, 0, 15, 111, 0, 31, 3, 7, 1, 0, 0, 105, 7, 72, 0, 0, 0, 0, 0, 1, 7, 0,
    0, 23, 5, 1, 0, 3, 1, 3, 0, 0, 7, 13, 0, 0, 0, 17, 35, 0, 0, 0, 115, 0};
const uint16_t kTunedUnit[] = {
    0, 37388, 178, 231, 2314, 328, 403, 441, 8655, 55809, 50, 47, 140, 242, 239, 313, 4512, 422,
    16860, 58511, 37, 93, 123, 210, 223, 297, 4496, 406, 25036, 58375, 81, 95, 16508, 39177, 220, 293,
    348, 437, 16891, 60031, 52, 30, 153, 4336, 24782, 48396, 417, 439, 16877, 62127, 25, 36870, 149, 170,
    235, 16691, 49471, 375, 25005, 61445, 71, 34053, 100, 179, 200, 2317, 4432, 388, 25018, 64778, 64, 38156,
    177, 230, 2311, 16710, 51469, 54538, 53767, 26, 132, 180, 248, 286, 335, 372, 25002, 57866, 70, 129,
    110, 211, 255, 45057, 317, 497, 376, 16814, 58047, 18, 32775, 16509, 40207, 16662, 49679, 469, 16780, 53903,
    5, 31, 154, 16625, 43522, 47113, 301, 465, 503, 16782, 54719, 38, 2061, 121, 4320, 253, 295, 4448,
    358, 24988, 57351, 36, 79, 16539, 41999, 45316, 16680, 49279, 484, 16779, 61551, 6, 78, 137, 4288, 43583,
    316, 449, 487, 24958, 63492, 35, 2063, 16522, 41231, 47621, 299, 369, 359, 24989, 58630, 16, 33039, 167,
    233, 2319, 16724, 52495, 57615, 66, 33295, 183, 202, 4384, 16726, 52231, 473, 495, 69, 63, 16491, 38367,
    245, 2307, 49158, 4576, 470, 24941, 53254, 16426, 33855, 187, 16620, 46351, 434, 25048, 61709, 58, 16485, 38922,
    218, 305, 341, 468, 24955, 61961, 41, 115, 4256, 197, 273, 16684, 51717, 499, 16778, 62559, 83, 46,
    105, 20688, 44335, 303, 386, 424, 16862, 62911, 1, 91, 16534, 38111, 229, 274, 302, 354, 392, 25022,
    53508, 72, 145, 16526, 41487, 282, 329, 419, 457, 479, 74, 148, 181, 217, 287, 337, 404, 25050,
    62730, 34, 92, 152, 193, 16606, 48143, 498, 377, 399, 51695, 57, 37900, 162, 199, 280, 16707, 51207,
    471, 24942, 64516, 7, 16459, 37263, 184, 250, 16673, 48607, 4592, 486, 24957, 55302, 24, 4224, 157, 24771,
    44038, 283, 331, 451, 25081, 59403, 22, 4192, 139, 225, 238, 311, 4464, 374, 16812, 52367, 67, 76,
    120, 16575, 39103, 277, 20800, 49410, 420, 25066, 56330, 48, 35343, 168, 247, 284, 332, 467, 16746, 53599,
    10, 116, 164, 216, 285, 334, 356, 16794, 63752, 40, 97, 126, 227, 6400, 314, 4544, 454, 16892,
    60815, 89, 131, 4272, 214, 18693, 50447, 16837, 62468, 56623, 84, 77, 16490, 39439, 279, 325, 371, 409,
    431, 49, 43, 16502, 36063, 213, 2306, 318, 370, 408, 25038, 54276, 20, 29, 103, 188, 252, 309,
    349, 485, 24940, 64007, 17, 35852, 161, 215, 281, 324, 355, 393, 415, 61935, 19, 59, 16518, 39951,
    2310, 322, 482, 361, 383, 85, 18443, 32911, 165, 16616, 46095, 433, 455, 509, 55743, 87, 98, 158,
    243, 43009, 45571, 2316, 333, 483, 24954, 55562, 53, 16497, 36991, 185, 203, 290, 343, 500, 16795, 51823,
    2, 2060, 135, 16558, 43279, 321, 450, 488, 8559, 56577, 9, 99, 159, 244, 2305, 315, 385, 391,
    16829, 63903, 55, 16412, 34159, 186, 204, 308, 347, 421, 16875, 58751, 54, 61, 119, 173, 205, 294,
    16734, 51343, 16842, 54367, 80, 34831, 166, 16633, 45103, 4560, 423, 16861, 60575, 39, 4208, 16525, 37599, 198,
    18692, 47727, 481, 360, 414, 64959, 86, 94, 156, 194, 16638, 45647, 401, 407, 25037, 59654, 23, 44,
    16492, 42255, 18697, 47279, 353, 502, 24973, 59910, 21, 45, 151, 189, 221, 310, 351, 501, 24956, 60679,
    65, 35087, 182, 201, 2318, 339, 452, 16747, 63583, 8, 130, 127, 16580, 41167, 16660, 50191, 389, 25035,
    60424, 56, 114, 111, 212, 4368, 298, 4528, 438, 16876, 64143, 51, 4240, 109, 226, 207, 312, 4480,
    390, 16828, 57487, 32, 36111, 40971, 219, 306, 344, 357, 16811, 53375, 82, 62, 122, 16593, 43055, 45407,
    418, 456, 510, 59599, 88, 146, 143, 228, 44289, 275, 319, 402, 440, 16878, 56511, 16457, 33794, 147,
    163, 246, 2312, 327, 387, 425, 447, 68, 2062, 136, 190, 16621, 47375, 466, 16888, 55855, 33, 27,
    102, 172, 44159, 291, 345, 373, 16827, 55423, 4, 37127, 133, 171, 251, 292, 346, 405, 16859, 59775,
    90, 117, 169, 234, 4400, 338, 436, 16890, 64607, 3, 60, 104, 16559, 39343, 2315, 330, 435, 489,
    511};
void build_schedule(Params& prm, int pairs) {
  for (int i = 0; i < kAttnUnits; i++) prm.blk[i] = (uint16_t)(i | 1 << 12);
  uint8_t delay[kMaxPairs] = {};
  static uint16_t lists[kMaxPairs][kMaxUnits];
  int n[kMaxPairs] = {};
  double t[kMaxPairs] = {};
  const double ta = 40.0, to = 59.0;
  for (int u = 0; u < kUnits; u++) {
    int p = 0;
    for (int q = 1; q < pairs; q++)
      if (t[q] < t[p] - 1e-9) p = q;
    uint16_t code;
    if (u < kAttnUnits) {
      code = (uint16_t)u;
    } else {
      const int o = u - kAttnUnits, g2 = o / 5, r = o % 5;
      code = (uint16_t)(0x800F | (r < 4 ? ((2 * g2 + (r >> 1)) << 2) | (r & 1) : ((2 * g2) << 2) | 2) << 8);
    }
    lists[p][n[p]++] = code;
    t[p] += u < kAttnUnits ? ta : to;
  }
  if (pairs == kTunedPairs) {
    for (int p = 0, o = 0; p < pairs; p++) {
      n[p] = kTunedLen[p];
      delay[p] = kTunedDelay[p];
      for (int i = 0; i < n[p]; i++) lists[p][i] = kTunedUnit[o++];
    }
    for (int i = 0; i < kAttnUnits; i++) prm.blk[i] = kTunedBlock[i];
  }
  int o = 0;
  for (int p = 0; p < pairs; p++) {
    prm.head[p] = o | n[p] << 10 | delay[p] << 15 | (uint32_t)(lists[p][0] & 511) << 23;
    for (int i = 0; i < n[p]; i++) prm.unit[o++] = lists[p][i];
  }
}

}

extern "C" void kernel_launch(void* const* d_in, const int* in_sizes, int n_in, void* d_out, int out_size) {
  (void)in_sizes; (void)n_in; (void)out_size;
  void* fnp = nullptr;
  cudaDriverEntryPointQueryResult qr;
  if (cudaGetDriverEntryPoint("cuTensorMapEncodeTiled", &fnp, cudaEnableDefault, &qr) != cudaSuccess || !fnp) return;
  EncodeFn fn = (EncodeFn)fnp;
  void* optr = nullptr;
  cudaGetSymbolAddress(&optr, g_o);
  Params prm;
  bool ok = true;
  for (int br = 0; br < 2; br++) {
    void* const* in = d_in + 5 * br;
    ok &= encode_2d(fn, &prm.x[br], in[0], (uint64_t)kB * kSq, kD, NQ);
    ok &= encode_kv(fn, &prm.kv[br], in[1]);
    ok &= encode_kv(fn, &prm.kv[2 + br], in[2]);
    ok &= encode_panels(fn, &prm.wq[br], in[3], kD, kH * kDh, 64);
    ok &= encode_panels(fn, &prm.wo[br], in[4], kH * kDh, kD, 64);
    prm.xp[br] = (const __nv_bfloat16*)in[0];
    prm.wp[br] = (const __nv_bfloat16*)in[3];
    prm.kp[br] = (const __nv_bfloat16*)in[1];
    prm.vp[br] = (const __nv_bfloat16*)in[2];
  }
  prm.op = (__nv_bfloat16*)d_out;
  ok &= encode_2d(fn, &prm.o_ld, optr, (uint64_t)kAttnUnits * 4 * kSq, 64, NQ, CU_TENSOR_MAP_SWIZZLE_NONE);
  ok &= encode_panels(fn, &prm.out, d_out, (uint64_t)kB * kSq, 2 * kD, ST_ROWS, 1);
  if (!ok) return;
  cudaFuncSetAttribute(mha_fused_kernel, cudaFuncAttributeMaxDynamicSharedMemorySize, SMEM_BYTES);
  cudaLaunchConfig_t cfg = {};
  cfg.gridDim = dim3(2);
  cfg.blockDim = dim3(384);
  cfg.dynamicSmemBytes = SMEM_BYTES;
  cfg.stream = cudaStreamPerThread;
  int pairs = 0;
  if (cudaOccupancyMaxActiveClusters(&pairs, mha_fused_kernel, &cfg) != cudaSuccess || pairs < 1) return;
  if (pairs > kMaxPairs) pairs = kMaxPairs;
  if (pairs < 24) return;
  build_schedule(prm, pairs);
  mha_fused_kernel<<<2 * pairs, 384, SMEM_BYTES, cudaStreamPerThread>>>(prm);
}
```

```cpp
#include <cuda_runtime.h>
#include <cuda_bf16.h>
#include <cuda.h>
#include <stdint.h>

namespace {

constexpr int kB = 16, kSq = 224, kD = 640, kH = 32, kSk = 1024, kDh = 128;
constexpr int kGroups = 2 * kB;
constexpr int kAttnUnits = kGroups * kH / 2;
constexpr int kOutUnits = kGroups * 5 / 2;
constexpr int kUnits = kAttnUnits + kOutUnits;
constexpr int kMaxUnits = kUnits + 64;
constexpr int kMaxPairs = 72;
constexpr int NQ = 112;
constexpr int PANEL = NQ * 128;
constexpr float kQScale = 0.08838834764831845f * 1.4426950408889634f;
constexpr int SLOT = 16384;
constexpr int NSLOT = 7;

constexpr int SM_PANEL = 0;
constexpr int SM_RING = SM_PANEL + 8 * PANEL;
constexpr int NBAR = NSLOT + 8;
constexpr int SM_RCP = SM_RING + NSLOT * SLOT;
constexpr int SM_BAR = SM_RCP + 640;
constexpr int SM_END = SM_BAR + 8 * (2 * NBAR + 12) + 32;
constexpr int SMEM_BYTES = SM_END + 1024;
static_assert(SM_RING % 1024 == 0 && PANEL % 1024 == 0, "swizzle alignment");
static_assert(SMEM_BYTES <= 232448, "smem");

struct Params {
  CUtensorMap x[2], wq[2], kv[4], wo[2];
  CUtensorMap o_ld, out;
  const __nv_bfloat16* xp[2];
  const __nv_bfloat16* wp[2];
  const __nv_bfloat16* kp[2];
  const __nv_bfloat16* vp[2];
  __nv_bfloat16* op;
  uint32_t head[kMaxPairs];
  uint16_t unit[kMaxUnits];
  uint16_t blk[kAttnUnits];
};

struct Unit {
  bool attn, mc;
  int g, hc;
  int h0, nslab;
};
__device__ __forceinline__ int unit_slabs(uint32_t u) {
  return (u & 0x8000u) ? 4 * ((u & 15) + 1 - ((u >> 4) & 15)) : kD / 64;
}
__device__ __forceinline__ Unit decode_unit(uint32_t u, uint32_t rank) {
  Unit r;
  r.attn = !(u & 0x8000u);
  r.nslab = unit_slabs(u);
  if (r.attn) {
    r.g = (u >> 4) & 31;
    r.hc = (u & 15) * 2 + rank;
    r.mc = true;
    r.h0 = 0;
  } else {
    const uint32_t t = (u >> 8) & 3;
    r.mc = t < 2;
    r.g = ((u >> 10) & 31) + (t < 2 ? 0 : rank);
    r.hc = t < 2 ? 2 * t + rank : 4;
    r.h0 = (u >> 4) & 15;
  }
  return r;
}

__device__ uint4 g_qrow[2 * kMaxPairs * 2 * 16 * 128];
__device__ unsigned int g_pc[128 * 16 * 2];
__device__ __nv_bfloat16 g_o[(size_t)kAttnUnits * kSq * 2 * kDh];
__device__ unsigned int g_ticket;
__device__ unsigned int g_rd[kAttnUnits];
__device__ unsigned int g_cnt[kAttnUnits];

constexpr int CREGS = 232, SM_OFF = -1, ST_ROWS = 56;
template <bool V>
struct BoolC {
  static constexpr bool value = V;
};
template <int V>
struct IntC {
  static constexpr int value = V;
};
template <int I, int N, class F>
__device__ __forceinline__ void static_for(F&& f) {
  if constexpr (I < N) {
    f(IntC<I>{});
    static_for<I + 1, N>(f);
  }
}
constexpr uint32_t kPat0 = 04321432100, kPat1 = 04302102100;
__host__ __device__ constexpr int x_pos(int pat, int k) { return ((pat == 0 ? kPat0 : kPat1) >> 3 * k) & 7; }
__host__ __device__ constexpr int x_off(int pat, int k) { return k == 0 ? 0 : x_off(pat, k - 1) + (x_pos(pat, k - 1) == 0 ? 3 : 1); }
__host__ __device__ constexpr int w_cut(int i) { return 56 * i / 5; }
__device__ __forceinline__ uint32_t unit_pattern(uint32_t u, uint32_t prev) {
  return (prev & 0x8000u) && unit_slabs(u) >= 10 ? kPat1 : kPat0;
}
__device__ __forceinline__ uint32_t next_pos(uint32_t pos, int k, uint32_t pat) {
  return k < 9 ? (pat >> (3 * k + 3)) & 7 : (pos & 3) + 1;
}
__device__ __forceinline__ uint32_t pick(bool c, uint32_t a, uint32_t b) {
  uint32_t r;
  asm("{\n.reg .pred p;\nsetp.ne.u32 p, %1, 0;\nselp.u32 %0, %2, %3, p;\n}" : "=r"(r) : "r"((uint32_t)c), "r"(a), "r"(b));
  return r;
}
__device__ __forceinline__ uint32_t ring_round(uint32_t i) { return (i * 9363u) >> 16; }
__device__ __forceinline__ uint32_t ring_slot(uint32_t i) { return i - NSLOT * ring_round(i); }
__device__ __forceinline__ uint32_t ring_par(uint32_t i) { return ring_round(i) & 1; }

__device__ __forceinline__ uint32_t smem_u32(const void* p) { return (uint32_t)__cvta_generic_to_shared(p); }
__device__ __forceinline__ void mbar_init(uint32_t bar, uint32_t cnt) {
  asm volatile("mbarrier.init.shared::cta.b64 [%0], %1;" ::"r"(bar), "r"(cnt));
}
__device__ __forceinline__ void mbar_arrive1_if(uint32_t bar, bool pred) {
  asm volatile("{\n.reg .pred p;\nsetp.ne.u32 p, %1, 0;\n@p mbarrier.arrive.shared::cta.b64 _, [%0];\n}" ::"r"(bar), "r"((uint32_t)pred)
               : "memory");
}
__device__ __forceinline__ void mbar_wait_warp(uint32_t bar, uint32_t parity) {
  asm volatile(
      "{\n.reg .pred p, q;\n.reg .u32 c;\n"
      "mov.u32 c, 0;\n"
      "SPIN:\n"
      "mbarrier.try_wait.parity.shared::cta.b64 p, [%0], %1;\n"
      "vote.sync.all.pred q, p, 0xffffffff;\n"
      "@q bra.uni DONE;\n"
      "add.u32 c, c, 1;\n"
      "setp.gt.u32 q, c, 0x1000000;\n"
      "@q trap;\n"
      "bra.uni SPIN;\n"
      "DONE:\n}" ::"r"(bar),
      "r"(parity)
      : "memory");
}
__device__ __forceinline__ uint32_t mbar_test(uint32_t bar, uint32_t parity) {
  uint32_t ok;
  asm volatile(
      "{\n.reg .pred p;\nmbarrier.test_wait.parity.shared::cta.b64 p, [%1], %2;\nselp.u32 %0, 1, 0, p;\n}"
      : "=r"(ok)
      : "r"(bar), "r"(parity)
      : "memory");
  return ok;
}
__device__ __forceinline__ uint32_t mbar_test_if(uint32_t bar, uint32_t parity, bool pred) {
  uint32_t ok;
  asm volatile(
      "{\n.reg .pred p, q;\nsetp.ne.u32 q, %3, 0;\nsetp.eq.u32 p, %3, 0;\n"
      "@q mbarrier.test_wait.parity.shared::cta.b64 p, [%1], %2;\nselp.u32 %0, 1, 0, p;\n}"
      : "=r"(ok)
      : "r"(bar), "r"(parity), "r"((uint32_t)pred)
      : "memory");
  return ok;
}
#define ELECTED "{\n.reg .pred e;\nelect.sync _|e, 0xffffffff;\n@e "
constexpr uint64_t kEvictFirst = 0x12F0000000000000ull, kEvictNormal = 0x1000000000000000ull;
__device__ __forceinline__ void flag_wait(const unsigned int* p, uint32_t target) {
  asm volatile(
      "{\n.reg .pred p, q;\n.reg .u32 c, v;\n"
      "mov.u32 c, 0;\n"
      "SPIN:\n"
      "ld.acquire.gpu.global.u32 v, [%0];\n"
      "setp.ge.u32 p, v, %1;\n"
      "vote.sync.all.pred q, p, 0xffffffff;\n"
      "@q bra.uni DONE;\n"
      "nanosleep.u32 200;\n"
      "add.u32 c, c, 1;\n"
      "setp.gt.u32 q, c, 0x1000000;\n"
      "@q trap;\n"
      "bra.uni SPIN;\n"
      "DONE:\n}" ::"l"(p),
      "r"(target)
      : "memory");
}
__device__ __forceinline__ uint32_t flags_wait(const unsigned int* p, uint32_t target, uint32_t need) {
  uint32_t m;
  asm volatile(
      "{\n.reg .pred p, q;\n.reg .u32 c, v;\n"
      "mov.u32 c, 0;\n"
      "SPIN:\n"
      "ld.acquire.gpu.global.u32 v, [%1];\n"
      "setp.ge.u32 p, v, %2;\n"
      "vote.sync.ballot.b32 %0, p, 0xffffffff;\n"
      "and.b32 v, %0, %3;\n"
      "setp.eq.u32 q, v, %3;\n"
      "@q bra.uni DONE;\n"
      "add.u32 c, c, 1;\n"
      "setp.gt.u32 q, c, 0x1000000;\n"
      "@q trap;\n"
      "bra.uni SPIN;\n"
      "DONE:\n"
      "fence.proxy.async.global;\n}"
      : "=&r"(m)
      : "l"(p), "r"(target), "r"(need)
      : "memory");
  return m;
}
__device__ __forceinline__ void e_arrive(uint32_t bar, uint32_t n) {
  asm volatile(ELECTED "mbarrier.arrive.shared::cta.b64 _, [%0], %1;\n}" ::"r"(bar), "r"(n) : "memory");
}
__device__ __forceinline__ void e_expect_tx(uint32_t bar, uint32_t bytes) {
  asm volatile(ELECTED "mbarrier.arrive.expect_tx.shared::cta.b64 _, [%0], %1;\n}" ::"r"(bar), "r"(bytes) : "memory");
}
__device__ __forceinline__ void tma_ld2(uint32_t dst, const CUtensorMap* m, int c0, int c1, uint32_t bar, uint64_t pol) {
  asm volatile(ELECTED
               "cp.async.bulk.tensor.2d.shared::cluster.global.mbarrier::complete_tx::bytes.L2::cache_hint [%0], [%1, {%3, %4}], "
               "[%2], %5;\n}" ::"r"(dst),
               "l"(m), "r"(bar), "r"(c0), "r"(c1), "l"(pol)
               : "memory");
}
__device__ __forceinline__ void tma_ld2_mc(uint32_t dst, const CUtensorMap* m, int c0, int c1, uint32_t bar, uint64_t pol) {
  asm volatile(ELECTED
               "cp.async.bulk.tensor.2d.shared::cluster.global.mbarrier::complete_tx::bytes.multicast::cluster.L2::cache_hint "
               "[%0], [%1, {%3, %4}], [%2], %5, %6;\n}" ::"r"(dst),
               "l"(m), "r"(bar), "r"(c0), "r"(c1), "h"((uint16_t)3), "l"(pol)
               : "memory");
}
__device__ __forceinline__ void tma_ld3(uint32_t dst, const CUtensorMap* m, int c1, int c2, uint32_t bar, uint64_t pol) {
  asm volatile(ELECTED
               "cp.async.bulk.tensor.3d.shared::cluster.global.mbarrier::complete_tx::bytes.L2::cache_hint [%0], [%1, {%3, %4, "
               "%5}], [%2], %6;\n}" ::"r"(dst),
               "l"(m), "r"(bar), "r"(0), "r"(c1), "r"(c2), "l"(pol)
               : "memory");
}
__device__ __forceinline__ void tma_ld4(uint32_t dst, const CUtensorMap* m, int c3, uint32_t bar, uint64_t pol) {
  asm volatile(ELECTED
               "cp.async.bulk.tensor.4d.shared::cluster.global.mbarrier::complete_tx::bytes.L2::cache_hint [%0], [%1, {%3, %3, "
               "%3, %4}], [%2], %5;\n}" ::"r"(dst),
               "l"(m), "r"(bar), "r"(0), "r"(c3), "l"(pol)
               : "memory");
}
__device__ __forceinline__ void tma_st3(const CUtensorMap* m, int c1, int c2, uint32_t src, bool add) {
  if (add)
    asm volatile(ELECTED "cp.reduce.async.bulk.tensor.3d.global.shared::cta.add.bulk_group [%0, {%2, %3, %4}], [%1];\n}" ::"l"(m), "r"(src),
                 "r"(0), "r"(c1), "r"(c2)
                 : "memory");
  else
    asm volatile(ELECTED "cp.async.bulk.tensor.3d.global.shared::cta.bulk_group [%0, {%2, %3, %4}], [%1];\n}" ::"l"(m), "r"(src), "r"(0),
                 "r"(c1), "r"(c2)
                 : "memory");
}
__device__ __forceinline__ void wgmma_fence() { asm volatile("wgmma.fence.sync.aligned;" ::: "memory"); }
__device__ __forceinline__ void wgmma_commit() { asm volatile("wgmma.commit_group.sync.aligned;" ::: "memory"); }
template <int N>
__device__ __forceinline__ void wgmma_wait() {
  asm volatile("wgmma.wait_group.sync.aligned %0;" ::"n"(N) : "memory");
}
template <int N>
__device__ __forceinline__ void wgmma_wait_pin(int never, int c) {
  asm volatile("{\n.reg .pred p;\nsetp.eq.u32 p, %1, %2;\nAGAIN:\nwgmma.wait_group.sync.aligned %0;\n@p bra.uni AGAIN;\n}" ::"n"(N),
               "r"(never), "r"(c)
               : "memory");
}
__device__ __forceinline__ void pin_order(int never, int c) {
  asm volatile("{\n.reg .pred p;\nsetp.eq.u32 p, %0, %1;\nAGAIN:\n@p nanosleep.u32 1;\n@p bra.uni AGAIN;\n}" ::"r"(never), "r"(c) : "memory");
}
template <int N>
__device__ __forceinline__ void fence_regs(float (&d)[N]) {
#pragma unroll
  for (int i = 0; i < N; i++) asm volatile("" : "+f"(d[i])::"memory");
}
__device__ __forceinline__ void fence_async_smem() { asm volatile("fence.proxy.async.shared::cta;" ::: "memory"); }
__device__ __forceinline__ void bar_sync(int id, int n) { asm volatile("bar.sync %0, %1;" ::"r"(id), "r"(n) : "memory"); }
__device__ __forceinline__ void bar_arrive(int id, int n) {
  asm volatile("bar.arrive %0, %1;" ::"r"(id), "r"(n) : "memory");
}
__device__ __forceinline__ void stsm_x4_t(uint32_t addr, uint32_t r0, uint32_t r1, uint32_t r2, uint32_t r3) {
  asm volatile("stmatrix.sync.aligned.m8n8.x4.trans.shared.b16 [%0], {%1, %2, %3, %4};" ::"r"(addr), "r"(r0), "r"(r1),
               "r"(r2), "r"(r3)
               : "memory");
}
__device__ __forceinline__ void stsm_x4_t_pin(uint32_t addr, uint32_t r0, uint32_t r1, uint32_t r2, uint32_t r3, int never, int c) {
  asm volatile(
      "{\n.reg .pred p;\nsetp.eq.u32 p, %5, %6;\nAGAIN:\n"
      "stmatrix.sync.aligned.m8n8.x4.trans.shared.b16 [%0], {%1, %2, %3, %4};\n@p bra.uni AGAIN;\n}" ::"r"(addr),
      "r"(r0), "r"(r1), "r"(r2), "r"(r3), "r"(never), "r"(c)
      : "memory");
}
__device__ __forceinline__ void stsm_x2_t(uint32_t addr, uint32_t r0, uint32_t r1) {
  asm volatile("stmatrix.sync.aligned.m8n8.x2.trans.shared.b16 [%0], {%1, %2};" ::"r"(addr), "r"(r0), "r"(r1) : "memory");
}
__device__ __forceinline__ void stsm_x2_t_pin(uint32_t addr, uint32_t r0, uint32_t r1, int never, int c) {
  asm volatile(
      "{\n.reg .pred p;\nsetp.eq.u32 p, %3, %4;\nAGAIN:\n"
      "stmatrix.sync.aligned.m8n8.x2.trans.shared.b16 [%0], {%1, %2};\n@p bra.uni AGAIN;\n}" ::"r"(addr),
      "r"(r0), "r"(r1), "r"(never), "r"(c)
      : "memory");
}
__device__ __forceinline__ uint32_t pack_bf16(float lo, float hi) {
  uint32_t r;
  asm("cvt.rn.bf16x2.f32 %0, %1, %2;" : "=r"(r) : "f"(hi), "f"(lo));
  return r;
}
__device__ __forceinline__ float ex2(float x) {
  float y;
  asm("ex2.approx.ftz.f32 %0, %1;" : "=f"(y) : "f"(x));
  return y;
}
__device__ __forceinline__ uint32_t mk_desc(uint32_t addr) { return (1u << 16) | ((addr & 0x3FFFFu) >> 4); }

template <int TA, int TB = 0, int KV = 0>
__device__ __forceinline__ void wgmma_n112(float (&d)[56], uint32_t descA, uint32_t descB, int scaleD) {
  asm volatile(
      "{\n.reg .pred p;\n.reg .b32 hi, hb;\n.reg .b64 da, db;\nsetp.ne.b32 p, %58, 0;\n"
      "mov.b32 hi, %62;\nmov.b32 hb, %61;\nmov.b64 da, {%56, hi};\nmov.b64 db, {%57, hb};\n"
      "wgmma.mma_async.sync.aligned.m64n112k16.f32.bf16.bf16 "
      "{%0, %1, %2, %3, %4, %5, %6, %7, %8, %9, %10, %11, %12, %13, "
      "%14, %15, %16, %17, %18, %19, %20, %21, %22, %23, %24, %25, %26, %27, "
      "%28, %29, %30, %31, %32, %33, %34, %35, %36, %37, %38, %39, %40, %41, "
      "%42, %43, %44, %45, %46, %47, %48, %49, %50, %51, %52, %53, %54, %55}, "
      "da, db, p, 1, 1, %59, %60;\n}\n"
      : "+f"(d[0]), "+f"(d[1]), "+f"(d[2]), "+f"(d[3]), "+f"(d[4]), "+f"(d[5]), "+f"(d[6]),
        "+f"(d[7]), "+f"(d[8]), "+f"(d[9]), "+f"(d[10]), "+f"(d[11]), "+f"(d[12]), "+f"(d[13]),
        "+f"(d[14]), "+f"(d[15]), "+f"(d[16]), "+f"(d[17]), "+f"(d[18]), "+f"(d[19]), "+f"(d[20]),
        "+f"(d[21]), "+f"(d[22]), "+f"(d[23]), "+f"(d[24]), "+f"(d[25]), "+f"(d[26]), "+f"(d[27]),
        "+f"(d[28]), "+f"(d[29]), "+f"(d[30]), "+f"(d[31]), "+f"(d[32]), "+f"(d[33]), "+f"(d[34]),
        "+f"(d[35]), "+f"(d[36]), "+f"(d[37]), "+f"(d[38]), "+f"(d[39]), "+f"(d[40]), "+f"(d[41]),
        "+f"(d[42]), "+f"(d[43]), "+f"(d[44]), "+f"(d[45]), "+f"(d[46]), "+f"(d[47]), "+f"(d[48]),
        "+f"(d[49]), "+f"(d[50]), "+f"(d[51]), "+f"(d[52]), "+f"(d[53]), "+f"(d[54]), "+f"(d[55])
      : "r"(descA), "r"(descB), "r"(scaleD), "n"(TA), "n"(TB), "n"(TB ? 8 : 0x40000040), "n"(KV ? 0x40000080 : 0x40000040));
}

template <int T>
__device__ __forceinline__ void pack_half(float (&pk)[56], const float (&a)[56]) {
#pragma unroll
  for (int i = 0; i < 28; i++) pk[28 * T + i] = __uint_as_float(pack_bf16(a[2 * i], a[2 * i + 1]));
}
template <int T>
__device__ __forceinline__ void fence_half(float (&pk)[56]) {
#pragma unroll
  for (int i = 0; i < 28; i++) asm volatile("" : "+f"(pk[28 * T + i])::"memory");
}
template <int T, int LO = 0, int HI = 7>
__device__ __forceinline__ void store_half(uint32_t addr, const float (&pk)[56]) {
#pragma unroll
  for (int q = LO; q < HI; q++) {
    const float* r = pk + 28 * T + 4 * q;
    stsm_x4_t(addr + T * PANEL + q * 2048, __float_as_uint(r[0]), __float_as_uint(r[1]), __float_as_uint(r[2]), __float_as_uint(r[3]));
  }
}

template <int T>
__device__ __forceinline__ void q_half(uint32_t addr, float (&pk)[56], const float (&a)[56], int never) {
#pragma unroll
  for (int q = 0; q < 7; q++) {
    uint32_t r[4];
#pragma unroll
    for (int i = 0; i < 4; i++) {
      r[i] = pack_bf16(a[8 * q + 2 * i] * kQScale, a[8 * q + 2 * i + 1] * kQScale);
      pk[28 * T + 4 * q + i] = __uint_as_float(r[i]);
      if (T == 0 && (i == 1 || (i == 3 && q == 6))) stsm_x2_t(addr + q * 2048 + (i >> 1) * 1024, r[i - 1], r[i]);
    }
    if (T == 0 && q < 6) stsm_x2_t_pin(addr + q * 2048 + 1024, r[2], r[3], never, 4 + 4 * q);
    if (T == 1 && q < 6) stsm_x4_t_pin(addr + PANEL + q * 2048, r[0], r[1], r[2], r[3], never, 30 + 2 * q);
    if (T == 1 && q == 6) stsm_x4_t(addr + PANEL + q * 2048, r[0], r[1], r[2], r[3]);
  }
}

__device__ __forceinline__ float bf_lo(uint32_t u) { return __uint_as_float(u << 16); }
__device__ __forceinline__ float bf_hi(uint32_t u) { return __uint_as_float(u & 0xFFFF0000u); }

__device__ __forceinline__ void fma8(float* o, float a, const uint4& w, float c) {
  o[0] = fmaf(a, bf_lo(w.x), o[0] * c), o[1] = fmaf(a, bf_hi(w.x), o[1] * c);
  o[2] = fmaf(a, bf_lo(w.y), o[2] * c), o[3] = fmaf(a, bf_hi(w.y), o[3] * c);
  o[4] = fmaf(a, bf_lo(w.z), o[4] * c), o[5] = fmaf(a, bf_hi(w.z), o[5] * c);
  o[6] = fmaf(a, bf_lo(w.w), o[6] * c), o[7] = fmaf(a, bf_hi(w.w), o[7] * c);
}
__device__ __forceinline__ void slow_rows(uint4* qrow, int tq, const __nv_bfloat16* xp, const __nv_bfloat16* wp,
                                          const __nv_bfloat16* kp, const __nv_bfloat16* vp, __nv_bfloat16* op) {
  if (tq >= NQ) return;
#pragma unroll 1
  for (int c = 0; c < 16; c++) {
    float q[8] = {};
#pragma unroll 1
    for (int k = 0; k < kD; k++)
      fma8(q, __bfloat162float(xp[tq * kD + k]), __ldg(reinterpret_cast<const uint4*>(wp + k * (kH * kDh)) + c), 1.f);
    qrow[c * 128] = make_uint4(pack_bf16(q[0] * kQScale, q[1] * kQScale), pack_bf16(q[2] * kQScale, q[3] * kQScale),
                               pack_bf16(q[4] * kQScale, q[5] * kQScale), pack_bf16(q[6] * kQScale, q[7] * kQScale));
  }
#pragma unroll 1
  for (int pass = 0; pass < 4; pass++) {
    float o[32] = {}, m = -INFINITY, l = 0.f;
#pragma unroll 1
    for (int key = 0; key < kSk; key++) {
      const uint4* kr = reinterpret_cast<const uint4*>(kp + key * kDh);
      const uint4* vr = reinterpret_cast<const uint4*>(vp + key * kDh) + 4 * pass;
      float s = 0.f;
#pragma unroll 1
      for (int c = 0; c < 16; c++) {
        const uint4 q = qrow[c * 128], k = __ldg(kr + c);
        s = fmaf(bf_lo(q.x), bf_lo(k.x), s); s = fmaf(bf_hi(q.x), bf_hi(k.x), s);
        s = fmaf(bf_lo(q.y), bf_lo(k.y), s); s = fmaf(bf_hi(q.y), bf_hi(k.y), s);
        s = fmaf(bf_lo(q.z), bf_lo(k.z), s); s = fmaf(bf_hi(q.z), bf_hi(k.z), s);
        s = fmaf(bf_lo(q.w), bf_lo(k.w), s); s = fmaf(bf_hi(q.w), bf_hi(k.w), s);
      }
      const float mn = fmaxf(m, s);
      const float ms = (mn == -INFINITY) ? 0.f : mn;
      const float corr = ex2(m - ms), p = ex2(s - ms);
      l = l * corr + p;
      m = mn;
      const float pb = __bfloat162float(__float2bfloat16(p));
#pragma unroll
      for (int c = 0; c < 4; c++) fma8(o + 8 * c, pb, __ldg(vr + c), corr);
    }
    const float sc = __fdividef(1.f, l);
    __nv_bfloat16* dst = op + (pass >> 1) * PANEL + (pass & 1) * 3584 + (tq >> 3) * 64 + (tq & 7);
#pragma unroll
    for (int d = 0; d < 32; d++) dst[(d >> 3) * 896 + (d & 7) * 8] = __float2bfloat16(o[d] * sc);
  }
}

__device__ __forceinline__ uint32_t launch_epoch() { return atomicAdd(&g_ticket, 1u) / gridDim.x; }

__global__ void __cluster_dims__(2, 1, 1) __launch_bounds__(384, 1) mha_fused_kernel(const __grid_constant__ Params prm) {
  extern __shared__ __align__(1024) unsigned char smem_raw[];

  const uint32_t sb = (smem_u32(smem_raw) + 1023u) & ~1023u;
  const uint32_t full0 = sb + SM_BAR, empty0 = full0 + 8 * NBAR, sfull0 = empty0 + 8 * NBAR;
  const uint32_t cred0 = sfull0 + 32, redo0 = cred0 + 64, epoch_addr = redo0 + 8, go_bar = redo0 + 16, ok_bar = redo0 + 24;
  const uint32_t rank = blockIdx.x & 1, pair = blockIdx.x >> 1;
  const uint32_t head = prm.head[pair];
  const int u_begin = head & 1023, u_end = u_begin + ((head >> 10) & 31);
  const uint32_t delay = ((head >> 15) & 255) * 256;
  const int tid = threadIdx.x;
  const int wid = __shfl_sync(0xffffffffu, tid >> 5, 0), wg = wid >> 2;

  if (wg == 2) {
    asm volatile("setmaxnreg.dec.sync.aligned.u32 %0;" ::"n"(504 - 2 * CREGS));
    const int warp = wid & 3, lane = tid & 31;
    bar_sync(0, 384);
    asm volatile("barrier.cluster.arrive.relaxed.aligned;" ::: "memory");
    if (warp < 3 && delay)
      asm volatile(
          "{\n.reg .pred p, q;\n.reg .u32 t0, t;\nmov.u32 t0, %%clock;\n"
          "SPIN:\nnanosleep.u32 100;\nmov.u32 t, %%clock;\nsub.u32 t, t, t0;\nsetp.lt.u32 p, t, %0;\n"
          "vote.sync.all.pred q, p, 0xffffffff;\n@q bra.uni SPIN;\n}" ::"r"(delay));
    auto slot_addr = [&](uint32_t i) { return sb + SM_RING + ring_slot(i) * SLOT; };
    auto full_bar = [&](uint32_t i) { return full0 + 8 * ring_slot(i); };
    const int count = (head >> 10) & 31;
    if (warp == 0) {
      uint32_t it = 6, prev = 0, code = head >> 23;
      auto acquire = [&](uint32_t i) { mbar_wait_warp(empty0 + 8 * ring_slot(i), ring_par(i) ^ 1); };
      uint32_t rblk = 0, rleft = 0;
      auto block_read = [&]() {
        asm volatile(ELECTED "red.relaxed.gpu.global.add.u32 [%0], 1;\n}" ::"l"(&g_rd[prm.blk[rblk] & 511]) : "memory");
        rblk++;
        rleft--;
      };
#pragma unroll 1
      for (int n = 1; n <= count; n++) {
        const uint32_t pat = unit_pattern(code, prev);
        const Unit u = decode_unit(code, rank);
        const int br = u.g >> 4;
        const CUtensorMap* mw = (u.attn ? prm.wq : prm.wo) + br;
        const int nslab = u.nslab;
#pragma unroll 1
        for (int k = n == 1 ? 2 : 0, pos = n == 1; k < nslab; k++) {
          const uint32_t i = it + (pos == 0);
          acquire(i);
          e_expect_tx(full_bar(i), SLOT);
          tma_ld3(slot_addr(i), mw, u.h0 * 256 + k * 64, u.hc * 2, full_bar(i), kEvictNormal);
          if (rleft && (k & 3) == 2 && k != 6) {
#pragma unroll 1
            do block_read();
            while (rleft && k == 2);
          }
          if (!u.attn && k == 4) rblk = u.g * 16 + u.h0, rleft = nslab >> 2;
          it = i + 1 + (pos == 0);
          pos = next_pos(pos, k, pat);
        }
        if (u.attn) {
          const int row0 = ((u.g & 15) * kH + u.hc) * kSk;
#pragma unroll 1
          for (int j = 0; j < kSk / 32; j++, it++) {
            acquire(it);
            e_expect_tx(full_bar(it), SLOT);
            const int isv = j == 31 || (j > 0 && !(j & 1));
            tma_ld4(slot_addr(it), &prm.kv[2 * isv + br], row0 / 8 + (((j + 1) >> 1) - isv) * 8, full_bar(it), kEvictFirst);
            if (j == kSk / 32 - 2) e_arrive(go_bar, 1);
          }
        }
        prev = code;
        code = prm.unit[u_begin + n];
      }
      if (rleft) {
        acquire(it + NSLOT - 1);
#pragma unroll 1
        while (rleft) block_read();
      }
    } else if (warp < 3) {
      asm volatile("barrier.cluster.wait.acquire.aligned;" ::: "memory");
      const int w = warp == 1 ? rank : rank ^ 1;
      uint32_t it = 6, nc = 0, pph = 0, go_ph = 0, prev = 0, code = head >> 23;
      const unsigned int* flags0 = g_cnt + (lane & 15);
      uint32_t peer_cred0;
      asm("mapa.shared::cluster.u32 %0, %1, %2;" : "=r"(peer_cred0) : "r"(cred0), "r"(rank ^ 1));
#pragma unroll 1
      for (int n = 1; n <= count; n++) {
        const uint32_t pat = unit_pattern(code, prev);
        Unit u = decode_unit(code, rank);
        const CUtensorMap* mx = u.attn ? &prm.x[u.g >> 4] : &prm.o_ld;
        const int nslab = u.nslab;
        const bool polls = !u.attn && (warp == 1 || !u.mc);
        uint32_t done = 0, ready = 0;
        if (polls) {
          asm volatile("ld.volatile.shared.u32 %0, [%1];" : "=r"(done) : "r"(epoch_addr) : "memory");
          done *= 2;
        }
        const unsigned int* flags;
        asm("add.u64 %0, %1, %2;" : "=l"(flags) : "l"(flags0), "l"((uint64_t)(uint32_t)(u.g * 64)));
        const uint64_t xpol = u.attn ? kEvictNormal : kEvictFirst;
        int xcol = n == 1 ? 128 : 0, xrow = (u.g & 15) * kSq + w * NQ;
#pragma unroll 1
        for (int k = n == 1 ? 2 : 0, pos = n == 1; k < nslab; k++) {
          if (polls && (k & 2) == 0) {
            const uint32_t hp = u.h0 + (k >> 2);
            if ((k & 1) == 0) {
              if (!(ready >> hp & 1)) ready = flags_wait(flags, done, 1u << hp);
              xrow = (prm.blk[u.g * 16 + hp] & 511) * (4 * kSq) + w * NQ;
            } else if (!(ready >> hp & 2)) {
              ready = flags_wait(flags, done, 0);
            }
          }
          const uint32_t i = it + 2 * w, q = pos - 1;
          const uint32_t fbar = full0 + 8 * (pos == 0 ? ring_slot(i) : NSLOT + 4 * w + q);
          const uint32_t dst = pos == 0 ? slot_addr(i) : sb + SM_PANEL + (4 * w + q) * PANEL;
          const uint32_t par = (pos == 0 ? ring_round(i) : pph >> q) & 1;
          pph ^= pos == 0 ? 0u : 1u << q;
          it += 1 + 2 * (pos == 0);
          pos = next_pos(pos, k, pat);
          mbar_wait_warp(fbar + 8 * NBAR, par ^ 1);
          e_expect_tx(fbar, PANEL);
          if (!u.mc) {
            tma_ld2(dst, mx, xcol, xrow, fbar, xpol);
          } else {
            if (warp == 1) {
              if (it > 10) mbar_wait_warp(cred0 + 8 * (nc & 7), (nc >> 3) & 1);
              tma_ld2_mc(dst, mx, xcol, xrow, fbar, xpol);
            } else if (it > 10) {
              asm volatile(ELECTED "mbarrier.arrive.shared::cluster.b64 _, [%0];\n}" ::"r"(peer_cred0 + 8 * (nc & 7)) : "memory");
            }
            nc += it > 10;
          }
          xcol += u.attn ? 64 : 0;
          xrow += u.attn ? 0 : kSq;
        }
        if (u.attn) {
          mbar_wait_warp(go_bar, go_ph);
          go_ph ^= 1;
          it += kSk / 32;
        }
        prev = code;
        code = prm.unit[u_begin + n];
      }
    } else {
      uint32_t epoch = 0, prev = 0;
      if (lane == 0) epoch = launch_epoch();
      epoch = __shfl_sync(0xffffffffu, epoch, 0);
      asm volatile("st.volatile.shared.u32 [%0], %1;" ::"r"(epoch_addr), "r"(epoch + 1) : "memory");
      auto publish = [&](unsigned int* p) {
        __syncwarp();
        asm volatile(ELECTED "red.release.gpu.global.add.u32 [%0], 1;\n}" ::"l"(p) : "memory");
      };
#pragma unroll 1
      for (int n = 0; n < count; n++) {
        const uint32_t code = prm.unit[u_begin + n], ph = n & 1;
        if (!(code & 0x8000u)) {
          const uint32_t blk = prm.blk[code & 511], gen = (blk >> 9) & 7;
          if (gen > 0) flag_wait(&g_rd[blk & 511], 5 * (epoch * (blk >> 12) + gen));
        }
        __syncwarp();
        e_arrive(ok_bar, 1);
        const uint32_t nx = n + 1 < count ? prm.unit[u_begin + n + 1] : 0;
        if (!(nx & 0x8000u) && (nx & 0x1800u)) {
          const Unit v = decode_unit(nx, rank);
          if (nx & 0x1000u) {
            const char* p = reinterpret_cast<const char*>(prm.xp[v.g >> 4] + ((v.g & 15) * kSq + rank * NQ) * kD) + lane * 128;
#pragma unroll 1
            for (int i = 0; i < NQ * kD * 2 / 4096; i++, p += 4096) {
              asm volatile("prefetch.global.L2 [%0];" ::"l"(p));
              __nanosleep(100);
            }
          }
          if (nx & 0x800u) {
            const char* p = reinterpret_cast<const char*>(prm.wp[v.g >> 4] + v.hc * kDh + (lane >> 1) * (kH * kDh)) + (lane & 1) * 128;
#pragma unroll 1
            for (int i = 0; i < kD / 16; i++, p += 16 * (kH * kDh * 2)) {
              asm volatile("prefetch.global.L2 [%0];" ::"l"(p));
              __nanosleep(100);
            }
          }
        }
        const bool clear = (code & 0xA000u) == 0x2000u;
        const uint32_t oc = clear ? nx : code;
        const Unit u = decode_unit(oc, rank);
        const int row = (u.g & 15) * kSq, cb = (u.g >> 4) * 10 + u.hc * 2;
        unsigned int* pc = g_pc + (oc >> 8 & 127) * 32 + rank;
        if (!(code & 0x8000u)) {
          if (clear) {
            uint4* o = reinterpret_cast<uint4*>(prm.op + (row + (lane >> 4)) * (2 * kD) + cb * 64) + (lane & 15);
#pragma unroll 1
            for (int r = 0; r < kSq / 2; r++, o += 4 * kD / 8) {
              *o = make_uint4(0, 0, 0, 0);
              __nanosleep(40);
            }
            publish(pc + 2 * (oc & 15));
          }
#pragma unroll 1
          for (int q = 0; q < 4; q++) mbar_wait_warp(sfull0 + 8 * q, ph);
          publish(&g_cnt[code & 511]);
        } else {
          const bool cleared = (prev & 0xA000u) == 0x2000u;
          if (u.h0) flag_wait(pc + 2 * (u.h0 - 1), epoch + 1);
          asm volatile("fence.proxy.async.global;" ::: "memory");
#pragma unroll 1
          for (int q = 0; q < 4; q++) {
            const int w = n + 1 < count ? q & 1 : q >> 1, t = n + 1 < count ? q >> 1 : q & 1;
            mbar_wait_warp(sfull0 + 8 * (2 * t + w), ph);
            fence_async_smem();
#pragma unroll 1
            for (int r = 0; r < NQ; r += ST_ROWS) {
              tma_st3(&prm.out, row + w * NQ + r, cb + t, sb + SM_PANEL + (4 * w + 2 + t) * PANEL + r * 128, u.h0 || cleared);
              asm volatile("cp.async.bulk.commit_group;" ::: "memory");
              if (n + 1 < count) asm volatile("cp.async.bulk.wait_group.read 0;" ::: "memory");
            }
            __syncwarp();
            e_arrive(empty0 + 8 * (NSLOT + 4 * w + 2 + t), 2);
          }
          if ((code & 15) != 15 && !cleared) {
            asm volatile("cp.async.bulk.wait_group 0;" ::: "memory");
            asm volatile("fence.proxy.async.global;" ::: "memory");
            publish(pc + 2 * (code & 15));
          }
        }
        prev = code;
      }
      asm volatile("cp.async.bulk.wait_group 0;" ::: "memory");
    }
  } else {
    const int tq = tid & 127, lane = tid & 31, warp = tq >> 5;
    if (tid == 0) {
#pragma unroll
      for (int i = 0; i < NBAR; i++) {
        mbar_init(full0 + 8 * i, 1);
        mbar_init(empty0 + 8 * i, 2);
      }
#pragma unroll
      for (int i = 0; i < 12; i++) mbar_init(sfull0 + 8 * i, i < 4 ? 4 : 1);
      mbar_init(go_bar, 1);
      mbar_init(ok_bar, 1);
      asm volatile("st.shared.v4.u32 [%0], {%1, %1, %1, %1};" ::"r"(redo0), "r"(0) : "memory");
      asm volatile("fence.mbarrier_init.release.cluster;" ::: "memory");
      fence_async_smem();
    }
    if (wid == 0) {
      __syncwarp();
      const Unit u = decode_unit(head >> 23, rank);
#pragma unroll
      for (int i = 0; i < 6; i++) {
        e_expect_tx(full0 + 8 * i, i % 3 == 1 ? SLOT : PANEL);
        if (i % 3 == 1) tma_ld3(sb + SM_RING + i * SLOT, &prm.wq[u.g >> 4], i / 3 * 64, u.hc * 2, full0 + 8 * i, kEvictNormal);
        else tma_ld2(sb + SM_RING + i * SLOT, &prm.x[u.g >> 4], i / 3 * 64, (u.g & 15) * kSq + i % 3 / 2 * NQ, full0 + 8 * i, kEvictNormal);
      }
    } else if (wid < 5) {
      asm volatile(ELECTED "prefetch.tensormap [%0];\n}" ::"l"(prm.x + 2 * (wid - 1) + (head >> 31)) : "memory");
    }
    bar_sync(0, 384);
    asm volatile("barrier.cluster.arrive.relaxed.aligned;" ::: "memory");
    asm volatile("setmaxnreg.inc.sync.aligned.u32 %0;" ::"n"(CREGS));
    const uint32_t stage = sb + SM_PANEL + wg * 4 * PANEL;
    const uint32_t st_q = __shfl_sync(
        0xffffffffu, stage + ((lane >> 4) * 8 + (lane & 7)) * 128 + (((2 * warp + ((lane >> 3) & 1)) ^ (lane & 7)) << 4), lane);
    const uint32_t st_p = st_q + 2 * PANEL;
    const uint32_t dq = mk_desc(stage), dring = mk_desc(sb + SM_RING);
    float acc[2][56], s[56] = {};
    const int never = (sb >> 24) & ~1u;
    uint32_t it = 0, pph = 0;
    auto wait_full = [&](uint32_t i) { mbar_wait_warp(full0 + 8 * ring_slot(i), ring_par(i)); };
    auto test = [&](uint32_t bar, uint32_t par) { return mbar_test_if(bar, par, warp == 0); };
    auto probe = [&](uint32_t i) { return test(full0 + 8 * ring_slot(i), ring_par(i)); };
    auto release = [&](uint32_t i) { mbar_arrive1_if(empty0 + 8 * ring_slot(i), tq == 0); };
    auto slot_desc = [&](uint32_t i) { return dring + ring_slot(i) * (SLOT >> 4); };
    if (wg == 1) bar_arrive(1, 256);

    struct Fin {
      uint32_t rp[16];
      char* dst;
    };
    uint32_t ps[14] = {};
    float l[28] = {};
    auto step_sums = [&]() {
#pragma unroll
      for (int g = 0; g < 14; g++) asm("add.rn.bf16x2 %0, %0, %1;" : "+r"(ps[g]) : "r"(pack_bf16(l[2 * g], l[2 * g + 1])));
#pragma unroll
      for (int q = 0; q < 3; q++) stsm_x4_t(st_p + q * 2048, ps[2 * q], ps[2 * q + 7], ps[2 * q + 1], ps[2 * q + 8]);
      stsm_x2_t(st_p + 3 * 2048, ps[6], ps[13]);
    };
    auto flag_bad = [&](bool bad) {
      asm volatile("{\n.reg .pred p;\nsetp.ne.u32 p, %1, 0;\n@p st.shared.u32 [%0], %1;\n}" ::"r"(redo0 + 4 * wg), "r"((uint32_t)bad)
                   : "memory");
    };
    auto step_finite = [&](bool live) {
      uint32_t z[4] = {0, 0, 0, 0};
#pragma unroll
      for (int i = 0; i < 28; i++)
        asm volatile("fma.rn.bf16x2 %0, %1, %2, %0;" : "+r"(z[i & 3]) : "r"(__float_as_uint(s[2 * i])), "r"(__float_as_uint(s[2 * i + 1])));
      asm volatile("add.rn.bf16x2 %0, %0, %1;" : "+r"(z[0]) : "r"(z[1]));
      asm volatile("add.rn.bf16x2 %0, %0, %1;" : "+r"(z[2]) : "r"(z[3]));
      asm volatile("add.rn.bf16x2 %0, %0, %1;" : "+r"(z[0]) : "r"(z[2]));
      flag_bad(live && (((z[0] & 0x7F807F80u) + 0x00800080u) & 0x80008000u));
    };
    auto rows_addr = [&]() {
      const uint32_t q = min(tq, NQ - 1), hi = q >= 56, n = q - 56 * hi;
      return stage + 2 * PANEL + n * 128 + ((hi ^ (n & 7)) << 4);
    };
    auto rows_load = [&](Fin& f, uint32_t a) {
#pragma unroll
      for (int c = 0; c < 4; c++)
        asm volatile("ld.shared.v4.u32 {%0, %1, %2, %3}, [%4];"
                     : "=r"(f.rp[4 * c]), "=r"(f.rp[4 * c + 1]), "=r"(f.rp[4 * c + 2]), "=r"(f.rp[4 * c + 3])
                     : "r"(a ^ (c << 5))
                     : "memory");
    };
    auto step_rows = [&](const Fin& f, bool live) {
      const uint32_t q = min(tq, NQ - 1);
      float t = 0.f, t2 = 0.f;
#pragma unroll
      for (int i = 0; i < 8; i++) {
        uint32_t v;
        asm("add.rn.bf16x2 %0, %1, %2;" : "=r"(v) : "r"(f.rp[2 * i]), "r"(f.rp[2 * i + 1]));
        t += bf_lo(v), t2 += bf_hi(v);
      }
      t += t2;
      float r;
      asm("rcp.approx.ftz.f32 %0, %1;" : "=f"(r) : "f"(t));
      asm volatile("st.shared.u16 [%0], %1;" ::"r"(sb + SM_RCP + wg * 320 + (q >> 1 & 3) * 80 + (q >> 3) * 4 + (q & 1) * 2),
                   "h"((uint16_t)pack_bf16(r, r))
                   : "memory");
      flag_bad(live && !(t >= 9.094947017729282e-13f && t <= 1.329227995784916e36f));
    };
    auto step_scales = [&](Fin& f) {
#pragma unroll
      for (int c = 0; c < 4; c++)
        asm volatile("ld.shared.v4.u32 {%0, %1, %2, %3}, [%4];"
                     : "=r"(f.rp[4 * c]), "=r"(f.rp[4 * c + 1]), "=r"(f.rp[4 * c + 2]), "=r"(f.rp[4 * c + 3])
                     : "r"(sb + SM_RCP + wg * 320 + (lane & 3) * 80 + c * 16)
                     : "memory");
    };
    auto o_base = [&](uint32_t u) {
      return reinterpret_cast<char*>(g_o) + (size_t)((((prm.blk[u & 511] & 511u) * 4 + rank * 2) * 2 + wg) * (uint32_t)PANEL);
    };
    auto step_write = [&](const Fin& f, int lo, int hi) {
#pragma unroll
      for (int i = lo; i < hi; i++) {
        uint32_t v = __float_as_uint(s[i]);
        asm("mul.rn.bf16x2 %0, %0, %1;" : "+r"(v) : "r"(f.rp[(i % 28) >> 1]));
        s[i] = __uint_as_float(v);
        asm volatile("st.global.u32 [%0], %1;" ::"l"(f.dst + (i / 28) * 2 * PANEL + (i & 1) * 1792 + ((i % 28) >> 1) * 128), "r"(v) : "memory");
      }
    };
    auto keep_alive = [&](int lo, int hi, int c) {
      if (never == c) {
#pragma unroll
        for (int i = lo; i < hi; i++) asm volatile("st.shared.f32 [%0], %1;" ::"r"(stage + 4 * i), "f"(s[i]) : "memory");
        pin_order(never, c);
      }
    };
    auto step_signal = [&](int t) {
      __syncwarp();
      mbar_arrive1_if(sfull0 + 8 * (2 * t + wg), lane == 0);
    };
    auto free_panel = [&](int q) { mbar_arrive1_if(empty0 + 8 * (NSLOT + 4 * wg + q), tq < 2); };
    auto read_verdict = [&]() {
      uint32_t redo;
      asm volatile("ld.shared.u32 %0, [%1];" : "=r"(redo) : "r"(redo0 + 4 * wg) : "memory");
      return redo;
    };
    auto step_redo = [&](uint32_t prev) {
      asm volatile("" : "+r"(prev));
      bar_sync(3 + wg, 128);
      if (tq == 0) asm volatile("st.shared.u32 [%0], %1;" ::"r"(redo0 + 4 * wg), "r"(0) : "memory");
      const Unit u = decode_unit(prev & 511, rank);
      const int br = u.g >> 4, b = u.g & 15;
      const size_t off = (size_t)(b * kH + u.hc) * kSk * kDh;
      slow_rows(g_qrow + (blockIdx.x * 2 + wg) * (16 * 128) + tq, tq, prm.xp[br] + (b * kSq + wg * NQ) * kD, prm.wp[br] + u.hc * kDh,
                prm.kp[br] + off, prm.vp[br] + off, reinterpret_cast<__nv_bfloat16*>(o_base(prev)));
#pragma unroll
      for (int i = 0; i < 56; i++) s[i] = 0.f;
    };
    auto issue_slab = [&](uint32_t da, uint32_t db, int accum, auto split, auto tb) {
      constexpr int TB = tb.value, KS = TB ? 224 : 2;
      if (TB) db += 111 << 16;
      if (split.value == 1) {
#pragma unroll
        for (int t = 0; t < 2; t++) {
#pragma unroll
          for (int kk = 0; kk < 4; kk++) {
            if (t == 1 && kk == 2) bar_arrive(2 - wg, 256);
            wgmma_n112<1, 0, 1>(acc[t], da + t * 64 + kk * 256, db + kk * KS, 1);
          }
          wgmma_commit();
        }
      } else {
#pragma unroll
        for (int kk = 0; kk < 4; kk++) {
          if (kk == 3) bar_arrive(2 - wg, 256);
          wgmma_n112<1, TB>(acc[0], da + kk * 128, db + kk * KS, kk > 0 ? 1 : accum);
          wgmma_n112<1, TB>(acc[1], da + 512 + kk * 128, db + kk * KS, kk > 0 ? 1 : accum);
        }
        wgmma_commit();
      }
    };

    uint32_t code = head >> 23, prev = 0, pend = 0, uph = 0;
    uint32_t da = slot_desc(1), db = slot_desc(2 * wg);
    auto next_unit = [&](bool block) {
      da = slot_desc(it + 1), db = slot_desc(it + 2 * wg);
      if (block) {
        if (!__all_sync(0xffffffffu, probe(it + 1) & probe(it + 2 * wg))) {
          wait_full(it + 1);
          wait_full(it + 2 * wg);
        }
      }
    };
    wait_full(1);
    wait_full(2 * wg);
    for (int left = (head >> 10) & 31; left > 0; left--) {
      const int ui = u_end - left;
      uint32_t nxt;
      bool defer;
      auto peek = [&]() {
        const uint32_t cur = prm.unit[ui];
        nxt = __shfl_sync(0xffffffffu, (uint32_t)prm.unit[ui + 1], 0);
        defer = left > 1 && (!(nxt & 0x8000u) || ((cur & 0x8000u) ? unit_slabs(nxt) >= 10 : cur & 0x4000u));
      };
      const bool out = code & 0x8000u;
      uint32_t rel = 0;
      auto retire = [&]() {
        wgmma_wait<0>();
        fence_regs(acc[0]);
        fence_regs(acc[1]);
        mbar_arrive1_if(rel, rel);
        rel = 0;
      };
      auto turn = [&](int accum, auto mode, auto tb, auto first) {
        bar_sync(1 + wg, 256);
        if (!first.value) retire();
        wgmma_fence();
        issue_slab(da, db, accum, mode, tb);
      };
      auto take_turn = [&](int accum, auto mode, auto first) {
        if (out) turn(accum, mode, IntC<1>{}, first);
        else turn(accum, mode, IntC<0>{}, first);
      };
      Fin f;
      take_turn(0, IntC<0>{}, BoolC<true>{});
      int k = 0;
      const bool staged = pend == 2;
      if (out ? pend == 1 : !staged) {
        uint32_t redo = 0;
        static_for<0, 8>([&](auto kc) {
          constexpr int k = kc.value;
          if (k > 0) take_turn(1, IntC<0>{}, BoolC<false>{});
          if (k >= 4) keep_alive(w_cut(k - 4), w_cut(k - 3), 62 + 2 * k);
          if (k == 2) step_scales(f);
          constexpr int p0 = x_pos(0, k), p1 = x_pos(0, k + 1), o0 = x_off(0, k), o1 = x_off(0, k + 1);
          const uint32_t rw = empty0 + 8 * ring_slot(it + o0 + (p0 == 0));
          const uint32_t rx = empty0 + 8 * (p0 == 0 ? ring_slot(it + o0 + 2 * wg) : NSLOT + 4 * wg + p0 - 1);
          const uint32_t wi = it + o1 + (p1 == 0), xi = it + o1 + 2 * wg;
          const uint32_t xbar = full0 + 8 * (p1 == 0 ? ring_slot(xi) : NSLOT + 4 * wg + p1 - 1);
          const uint32_t xpar = (p1 == 0 ? ring_round(xi) : pph >> (p1 == 0 ? 0 : p1 - 1)) & 1;
          if constexpr (p1 != 0) pph ^= 1u << (p1 - 1);
          uint32_t okp = probe(wi) & test(xbar, xpar);
          if (k == 2) okp &= test(ok_bar, uph ^ pend);
          rel = pick(tq == 0, rw, pick(tq < 3 && (k < 6 || out), rx, 0));
          if (k == 0) {
            uint32_t a = rows_addr();
            asm volatile("" : "+r"(a), "+r"(okp), "+r"(rel));
            if (pend) step_sums();
            bar_sync(3 + wg, 128);
            rows_load(f, a);
          }
          if (k == 1) {
            mbar_arrive1_if(empty0 + 8 * (NSLOT + 4 * wg + 2), tq < 2 && pend);
            step_rows(f, pend);
          }
          if (k == 2) {
            step_finite(pend);
            f.dst = o_base(prev) + warp * 3584 + lane * 4;
          }
          if (k == 6) redo = read_verdict();
          if (k >= 3 && pend) step_write(f, w_cut(k - 3), w_cut(k - 2));
          if (k == 7) {
            if (__any_sync(0xffffffffu, redo)) step_redo(prev);
            __syncwarp();
            mbar_arrive1_if(sfull0 + 8 * (2 * lane + wg), lane < 2 && pend);
          }
          const bool ok = __all_sync(0xffffffffu, okp);
          da = slot_desc(wi);
          db = p1 == 0 ? slot_desc(xi) : dq + (p1 - 1) * (PANEL >> 4);
          if (!ok) {
            retire();
            wait_full(wi);
            mbar_wait_warp(xbar, xpar);
            if (k == 2) mbar_wait_warp(ok_bar, uph ^ pend);
          }
        });
        k = 8;
        if (out) turn(1, IntC<0>{}, IntC<1>{}, BoolC<false>{});
      }
      const int nslab = unit_slabs(code);
      uint32_t pos = k ? 3 : 0, wi = it + (k ? 12 : 1), xbar = full0 + 8 * (k ? NSLOT + 4 * wg + 2 : ring_slot(it + 2 * wg));
      const int kend = nslab - 2;
      if (k < kend) {
        uint32_t r = it + (k ? 13 : 3);
        const uint32_t pat = staged ? kPat1 : kPat0;
        const uint32_t keep_pos = out ? 3 : 1;
        const int keep_k = out ? nslab - 4 : 5;
#pragma unroll 1
        while (true) {
          rel = pick(tq == 0, empty0 + 8 * ring_slot(wi), pick(tq < 3 && (pos < keep_pos || k < keep_k), xbar + 8 * NBAR, 0));
          pos = next_pos(pos, k, pat);
          const bool ring = pos == 0;
          const uint32_t i = r + 2 * wg, q = pos - 1;
          wi = ring ? r + 1 : r;
          xbar = full0 + 8 * (ring ? ring_slot(i) : NSLOT + 4 * wg + q);
          const uint32_t xpar = (ring ? ring_round(i) : pph >> q) & 1;
          da = slot_desc(wi);
          db = ring ? slot_desc(i) : dq + q * (PANEL >> 4);
          pph ^= ring ? 0u : 1u << q;
          r += ring ? 3 : 1;
          const bool ok = __all_sync(0xffffffffu, probe(wi) & test(xbar, xpar));
          if (staged && k < 2) {
            if (k == 0) {
              store_half<1, 0, 4>(st_p, s);
            } else {
              store_half<1, 4, 7>(st_p, s);
              step_signal(1);
            }
          }
          if (!ok) {
            retire();
            wait_full(wi);
            mbar_wait_warp(xbar, xpar);
          }
          if (++k == kend) break;
          take_turn(1, IntC<0>{}, BoolC<false>{});
        }
      }
      it += nslab + (staged ? 8 : 4);
      const uint32_t ql = out ? 1 : 3, xl = full0 + 8 * (NSLOT + 4 * wg + ql), pl = pph >> ql & 1, dl = slot_desc(it - 1);
      pph ^= 1u << ql;
      if (!__all_sync(0xffffffffu, probe(it - 1) & test(xl, pl))) {
        retire();
        wait_full(it - 1);
        mbar_wait_warp(xl, pl);
      }
      auto last_turn = [&](auto tb) {
        constexpr int TB = tb.value;
        bar_sync(1 + wg, 256);
        retire();
        wgmma_fence();
#pragma unroll
        for (int t = 0; t < 2; t++) {
#pragma unroll
          for (int kk = 0; kk < 8; kk++)
            wgmma_n112<1, TB>(acc[t], (kk < 4 ? da : dl) + t * 512 + (kk & 3) * 128,
                              db + t * never + (TB ? 111 << 16 : 0) + (kk >> 2) * (PANEL >> 4) + (kk & 3) * (TB ? 224 : 2), 1);
          wgmma_commit();
        }
        bar_arrive(2 - wg, 256);
      };
      const uint32_t rw2 = empty0 + 8 * pick(tq == 0, ring_slot(it - 2), ring_slot(it - 1));
      if (!out) {
        {
          last_turn(IntC<0>{});
          keep_alive(28, 56, 80);
          const bool ok = __all_sync(0xffffffffu, probe(it));
          rel = pick(tq < 2, rw2, 0);
          da = slot_desc(it);
          wgmma_wait<1>();
          fence_regs(acc[0]);
          q_half<0>(st_q, s, acc[0], never);
          wgmma_wait<0>();
          fence_regs(acc[1]);
          q_half<1>(st_q, s, acc[1], never);
          mbar_arrive1_if(rel, rel);
          if (!ok) wait_full(it);
        }
        fence_async_smem();
        auto issue_s = [&](uint32_t dk, int accum) {
          wgmma_fence();
#pragma unroll
          for (int kk = 0; kk < 8; kk++)
            wgmma_n112<0, 0, 1>(s, dk + (kk >> 2) * 64 + (kk & 3) * 2, dq + (kk >> 2) * (PANEL >> 4) + (kk & 3) * 2, kk > 0 ? 1 : accum);
          wgmma_commit();
        };
        auto add_sums = [&]() {
#pragma unroll
          for (int jj = 0; jj < 14; jj++)
            asm volatile("{\n.reg .b32 t;\nshl.b32 t, %2, 16;\nadd.f32 %0, %0, t;\nand.b32 t, %2, 0xffff0000;\nadd.f32 %1, %1, t;\n}"
                         : "+f"(l[2 * jj]), "+f"(l[2 * jj + 1])
                         : "r"(ps[jj]));
        };
        auto softmax = [&](uint32_t par, int pin0) {
          const uint32_t pa = st_p + par * PANEL;
#pragma unroll
          for (int i = 0; i < 4 + SM_OFF; i++) s[i] = ex2(s[i]);
#pragma unroll
          for (int jj = 0; jj < 14; jj++) {
#pragma unroll
            for (int i = 4 * jj + 4 + SM_OFF; i < 4 * jj + 8 + SM_OFF; i++)
              if (i < 56) s[i] = ex2(s[i]);
            const uint32_t p0 = pack_bf16(s[4 * jj], s[4 * jj + 1]), p1 = pack_bf16(s[4 * jj + 2], s[4 * jj + 3]);
            stsm_x2_t_pin(pa + jj * 1024, p0, p1, never, pin0);
            s[4 * jj] = __uint_as_float(p0), s[4 * jj + 1] = __uint_as_float(p1);
            asm("add.rn.bf16x2 %0, %1, %2;" : "=r"(ps[jj]) : "r"(p0), "r"(p1));
          }
        };
        bar_sync(1 + wg, 256);
        issue_s(da, never);
        bar_arrive(2 - wg, 256);
        {
#pragma unroll
          for (int i = 0; i < 28; i++) asm volatile("mov.b32 %0, 0;" : "=f"(l[i]));
          peek();
          const bool ok = __all_sync(0xffffffffu, probe(it + 1));
          da = slot_desc(it + 1);
          wgmma_wait_pin<0>(never, 180);
          fence_regs(s);
          release(it);
          softmax(0, 176);
          if (!ok) wait_full(it + 1);
        }
        it += 1;
#pragma unroll 1
        for (int j = 1; j < 16; j++) {
          fence_async_smem();
          bar_sync(1 + wg, 256);
          issue_s(da, 0);
          pin_order(never, 2 * j + 128);
          const uint32_t okv = mbar_test(full0 + 8 * ring_slot(it + 1), ring_par(it + 1));
          const uint32_t okk = probe(it + 2);
          da = slot_desc(it + 2);
          add_sums();
          const bool ok = __all_sync(0xffffffffu, okk);
          if (!__all_sync(0xffffffffu, okv)) wait_full(it + 1);
          {
            const uint32_t dv = slot_desc(it + 1), dp = dq + (3 - (j & 1)) * (PANEL >> 4);
            wgmma_fence();
#pragma unroll
            for (int kk = 0; kk < 4; kk++) {
              wgmma_n112<1, 0, 1>(acc[0], dv + kk * 256, dp + kk * 2, kk > 0 ? 1 : j > 1);
              wgmma_n112<1, 0, 1>(acc[1], dv + 64 + kk * 256, dp + kk * 2, kk > 0 ? 1 : j > 1);
            }
          }
          wgmma_commit();
          bar_arrive(2 - wg, 256);
          wgmma_wait<1>();
          fence_regs(s);
          release(it);
          softmax(j & 1, 2 * j + 192);
          wgmma_wait<0>();
          fence_regs(acc[0]);
          fence_regs(acc[1]);
          release(it + 1);
          it += 2;
          if (!ok) {
            wait_full(it);
          }
        }
        it += 1;
        fence_async_smem();
        bar_sync(1 + wg, 256);
        wgmma_fence();
        issue_slab(da, dq + 3 * (PANEL >> 4), 1, IntC<1>{}, IntC<0>{});
        pin_order(never, 182);
        mbar_arrive1_if(empty0 + 8 * (NSLOT + 4 * wg + (tq >> 1)), tq < 4);
        rel = pick(tq == 0, empty0 + 8 * ring_slot(it - 1), pick(tq < 3, empty0 + 8 * (NSLOT + 4 * wg + 3), 0));
        next_unit(defer);
        if (defer) {
          wgmma_wait<1>();
          fence_regs(acc[0]);
          pack_half<0>(s, acc[0]);
          fence_half<0>(s);
          wgmma_wait_pin<0>(never, 172);
          fence_regs(acc[1]);
          mbar_arrive1_if(rel, rel);
          pack_half<1>(s, acc[1]);
        }
        pend = 1;
      } else {
        last_turn(IntC<1>{});
        pin_order(never, 186);
        peek();
#pragma unroll
        for (int i = 0; i < 28; i++) ps[i >> 1] = 0, l[i] = 0.f;
        mbar_wait_warp(ok_bar, uph);
        next_unit(defer);
        rel = pick(tq < 2, rw2, pick(tq < 6, empty0 + 8 * (NSLOT + 4 * wg - 1 + (tq >> 1)), 0));
        wgmma_wait<1>();
        fence_regs(acc[0]);
        pack_half<0>(s, acc[0]);
        store_half<0>(st_p, s);
        step_signal(0);
        wgmma_wait<0>();
        fence_regs(acc[1]);
        mbar_arrive1_if(rel, rel);
        pack_half<1>(s, acc[1]);
        pend = 2;
      }
      if (!defer) {
        if (pend == 2) {
          store_half<1>(st_p, s);
        } else {
          step_sums();
          bar_sync(3 + wg, 128);
          rows_load(f, rows_addr());
          f.dst = o_base(code) + warp * 3584 + lane * 4;
          mbar_wait_warp(ok_bar, uph);
          step_rows(f, true);
          bar_sync(3 + wg, 128);
          step_scales(f);
          free_panel(2);
          retire();
          pack_half<0>(s, acc[0]);
          pack_half<1>(s, acc[1]);
          step_finite(true);
          step_write(f, 0, 28);
          bar_sync(3 + wg, 128);
          const uint32_t redo = read_verdict();
          step_write(f, 28, 56);
          if (__any_sync(0xffffffffu, redo)) step_redo(code);
          step_signal(0);
        }
        step_signal(1);
        pend = 0;
#pragma unroll
        for (int i = 0; i < 28; i++) ps[i >> 1] = 0, l[i] = 0.f;
        if (left > 1) {
          wait_full(it + 1);
          wait_full(it + 2 * wg);
        }
      }
      prev = code, code = nxt, uph ^= 1;
    }
    if (wg == 0) bar_sync(1, 256);
  }
}

typedef CUresult (*EncodeFn)(CUtensorMap*, CUtensorMapDataType, cuuint32_t, void*, const cuuint64_t*, const cuuint64_t*,
                             const cuuint32_t*, const cuuint32_t*, CUtensorMapInterleave, CUtensorMapSwizzle,
                             CUtensorMapL2promotion, CUtensorMapFloatOOBfill);

bool encode(EncodeFn fn, CUtensorMap* m, const void* ptr, int rank, const cuuint64_t* dims, const cuuint64_t* strides,
            const cuuint32_t* box, CUtensorMapL2promotion promo, CUtensorMapSwizzle swz = CU_TENSOR_MAP_SWIZZLE_128B) {
  const cuuint32_t es[4] = {1, 1, 1, 1};
  return fn(m, CU_TENSOR_MAP_DATA_TYPE_BFLOAT16, rank, const_cast<void*>(ptr), dims, strides, box, es,
            CU_TENSOR_MAP_INTERLEAVE_NONE, swz, promo,
            CU_TENSOR_MAP_FLOAT_OOB_FILL_NONE) == CUDA_SUCCESS;
}
bool encode_panels(EncodeFn fn, CUtensorMap* m, const void* ptr, uint64_t rows, uint64_t cols, uint32_t box_rows,
                   uint32_t box_blocks = 2) {
  const cuuint64_t dims[3] = {64, rows, cols / 64};
  const cuuint64_t strides[2] = {cols * 2, 128};
  const cuuint32_t box[3] = {64, box_rows, box_blocks};
  CUtensorMapL2promotion promo = CU_TENSOR_MAP_L2_PROMOTION_L2_128B;
  return encode(fn, m, ptr, 3, dims, strides, box, promo);
}
bool encode_kv(EncodeFn fn, CUtensorMap* m, const void* ptr) {
  const cuuint64_t dims[4] = {64, 8, 2, (uint64_t)kB * kH * kSk / 8};
  const cuuint64_t strides[3] = {kDh * 2, 128, 8 * kDh * 2};
  const cuuint32_t box[4] = {64, 8, 2, 8};
  CUtensorMapL2promotion promo = CU_TENSOR_MAP_L2_PROMOTION_L2_128B;
  return encode(fn, m, ptr, 4, dims, strides, box, promo);
}
bool encode_2d(EncodeFn fn, CUtensorMap* m, const void* ptr, uint64_t rows, uint64_t cols, uint32_t box_rows,
               CUtensorMapSwizzle swz = CU_TENSOR_MAP_SWIZZLE_128B) {
  const cuuint64_t dims[2] = {cols, rows};
  const cuuint64_t strides[1] = {cols * 2};
  const cuuint32_t box[2] = {64, box_rows};
  CUtensorMapL2promotion promo = CU_TENSOR_MAP_L2_PROMOTION_L2_128B;
  return encode(fn, m, ptr, 2, dims, strides, box, promo, swz);
}

constexpr int kTunedPairs = 66;
const uint16_t kTunedBlock[kAttnUnits] = {
    20480, 20486, 20492, 20498, 20504, 20510, 20516, 20522, 20528, 20534, 16444, 16450, 16456, 16462, 20996, 21002,
    20481, 20487, 20493, 20499, 20505, 20511, 20517, 20523, 20529, 20535, 16445, 16451, 16457, 16463, 20997, 21003,
    20482, 20488, 20494, 20500, 20506, 20512, 20518, 20524, 20530, 20536, 16446, 16452, 16458, 20992, 20998, 21004,
    20483, 20489, 20495, 20501, 20507, 20513, 20519, 20525, 20531, 20537, 16447, 16453, 16459, 20993, 20999, 21005,
    20484, 20490, 20496, 20502, 20508, 20514, 20520, 20526, 20532, 20538, 16448, 16454, 16460, 20994, 21000, 21006,
    20485, 20491, 20497, 20503, 20509, 20515, 20521, 20527, 20533, 20539, 16449, 16455, 16461, 20995, 21001, 21007,
    21008, 21012, 21016, 21020, 21024, 21028, 21032, 21036, 21040, 21044, 21048, 16956, 16960, 16964, 16968, 16972,
    21009, 21013, 21017, 21021, 21025, 21029, 21033, 21037, 21041, 21045, 21049, 16957, 16961, 16965, 16969, 16973,
    21010, 21014, 21018, 21022, 21026, 21030, 21034, 21038, 21042, 21046, 21050, 16958, 16962, 16966, 16970, 16974,
    21011, 21015, 21019, 21023, 21027, 21031, 21035, 21039, 21043, 21047, 21051, 16959, 16963, 16967, 16971, 16975,
    21504, 21506, 21508, 21510, 21512, 21514, 21516, 21518, 21520, 21522, 21524, 21526, 21528, 21530, 21532, 21534,
    21505, 21507, 21509, 21511, 21513, 21515, 21517, 21519, 21521, 21523, 21525, 21527, 21529, 21531, 21533, 21535,
    21536, 21540, 21544, 21548, 21552, 21556, 21560, 17468, 17472, 17476, 17480, 17484, 22016, 22020, 22024, 22028,
    21537, 21541, 21545, 21549, 21553, 21557, 21561, 17469, 17473, 17477, 17481, 17485, 22017, 22021, 22025, 22029,
    21538, 21542, 21546, 21550, 21554, 21558, 21562, 17470, 17474, 17478, 17482, 17486, 22018, 22022, 22026, 22030,
    21539, 21543, 21547, 21551, 21555, 21559, 21563, 17471, 17475, 17479, 17483, 17487, 22019, 22023, 22027, 22031,
    22032, 22034, 22036, 22038, 22040, 22042, 22044, 22046, 22048, 22050, 22052, 22054, 22056, 22058, 22060, 22062,
    22033, 22035, 22037, 22039, 22041, 22043, 22045, 22047, 22049, 22051, 22053, 22055, 22057, 22059, 22061, 22063,
    22064, 22066, 22068, 22070, 22072, 22074, 17980, 17982, 17984, 17986, 17988, 17990, 17992, 17994, 17996, 17998,
    22065, 22067, 22069, 22071, 22073, 22075, 17981, 17983, 17985, 17987, 17989, 17991, 17993, 17995, 17997, 17999,
    22528, 22529, 22530, 22531, 22532, 22533, 22534, 22535, 22536, 22537, 22538, 22539, 22540, 22541, 22542, 22543,
    22544, 22545, 22546, 22547, 22548, 22549, 22550, 22551, 22552, 22553, 22554, 22555, 22556, 22557, 22558, 22559,
    22560, 22570, 22580, 4178, 4188, 4198, 4208, 4218, 4228, 4238, 4248, 4258, 4268, 4278, 4288, 4298,
    22561, 22571, 22581, 4179, 4189, 4199, 4209, 4219, 4229, 4239, 4249, 4259, 4269, 4279, 4289, 4299,
    22562, 22572, 22582, 4180, 4190, 4200, 4210, 4220, 4230, 4240, 4250, 4260, 4270, 4280, 4290, 4300,
    22563, 22573, 22583, 4181, 4191, 4201, 4211, 4221, 4231, 4241, 4251, 4261, 4271, 4281, 4291, 4301,
    22564, 22574, 22584, 4182, 4192, 4202, 4212, 4222, 4232, 4242, 4252, 4262, 4272, 4282, 4292, 4302,
    22565, 22575, 22585, 4183, 4193, 4203, 4213, 4223, 4233, 4243, 4253, 4263, 4273, 4283, 4293, 4303,
    22566, 22576, 22586, 4184, 4194, 4204, 4214, 4224, 4234, 4244, 4254, 4264, 4274, 4284, 4294, 4304,
    22567, 22577, 22587, 4185, 4195, 4205, 4215, 4225, 4235, 4245, 4255, 4265, 4275, 4285, 4295, 4305,
    22568, 22578, 4176, 4186, 4196, 4206, 4216, 4226, 4236, 4246, 4256, 4266, 4276, 4286, 4296, 4306,
    22569, 22579, 4177, 4187, 4197, 4207, 4217, 4227, 4237, 4247, 4257, 4267, 4277, 4287, 4297, 4307};
const uint8_t kTunedLen[kTunedPairs] = {
    10, 10, 10, 10, 10, 10, 10, 9, 9, 11, 9, 11, 10, 10, 10, 10, 8, 9, 11, 8, 9, 10, 10, 11, 9, 9, 10, 10, 11, 10, 10, 11, 9,
    9, 10, 9, 9, 11, 10, 10, 9, 10, 11, 10, 10, 10, 10, 10, 9, 11, 10, 10, 10, 9, 10, 10, 10, 9, 10, 11, 10, 9, 10, 10, 9, 10};
const uint8_t kTunedDelay[kTunedPairs] = {
    0, 0, 0, 0, 0, 29, 5, 0, 105, 1, 0, 0, 1, 0, 1, 0, 0, 0, 0, 109, 109, 29,
    0, 0, 15, 111, 0, 31, 3, 7, 1, 0, 0, 105, 7, 72, 0, 0, 0, 0, 0, 1, 7, 0,
    0, 23, 5, 1, 0, 3, 1, 3, 0, 0, 7, 13, 0, 0, 0, 17, 35, 0, 0, 0, 115, 0};
const uint16_t kTunedUnit[] = {
    0, 37388, 178, 231, 2314, 328, 403, 441, 8655, 55809, 50, 47, 140, 242, 239, 313, 4512, 422,
    16860, 58511, 37, 93, 123, 210, 223, 297, 4496, 406, 25036, 58375, 81, 95, 16508, 39177, 220, 293,
    348, 437, 16891, 60031, 52, 30, 153, 4336, 24782, 48396, 417, 439, 16877, 62127, 25, 36870, 149, 170,
    235, 16691, 49471, 375, 25005, 61445, 71, 34053, 100, 179, 200, 2317, 4432, 388, 25018, 64778, 64, 38156,
    177, 230, 2311, 16710, 51469, 54538, 53767, 26, 132, 180, 248, 286, 335, 372, 25002, 57866, 70, 129,
    110, 211, 255, 45057, 317, 497, 376, 16814, 58047, 18, 32775, 16509, 40207, 16662, 49679, 469, 16780, 53903,
    5, 31, 154, 16625, 43522, 47113, 301, 465, 503, 16782, 54719, 38, 2061, 121, 4320, 253, 295, 4448,
    358, 24988, 57351, 36, 79, 16539, 41999, 45316, 16680, 49279, 484, 16779, 61551, 6, 78, 137, 4288, 43583,
    316, 449, 487, 24958, 63492, 35, 2063, 16522, 41231, 47621, 299, 369, 359, 24989, 58630, 16, 33039, 167,
    233, 2319, 16724, 52495, 57615, 66, 33295, 183, 202, 4384, 16726, 52231, 473, 495, 69, 63, 16491, 38367,
    245, 2307, 49158, 4576, 470, 24941, 53254, 16426, 33855, 187, 16620, 46351, 434, 25048, 61709, 58, 16485, 38922,
    218, 305, 341, 468, 24955, 61961, 41, 115, 4256, 197, 273, 16684, 51717, 499, 16778, 62559, 83, 46,
    105, 20688, 44335, 303, 386, 424, 16862, 62911, 1, 91, 16534, 38111, 229, 274, 302, 354, 392, 25022,
    53508, 72, 145, 16526, 41487, 282, 329, 419, 457, 479, 74, 148, 181, 217, 287, 337, 404, 25050,
    62730, 34, 92, 152, 193, 16606, 48143, 498, 377, 399, 51695, 57, 37900, 162, 199, 280, 16707, 51207,
    471, 24942, 64516, 7, 16459, 37263, 184, 250, 16673, 48607, 4592, 486, 24957, 55302, 24, 4224, 157, 24771,
    44038, 283, 331, 451, 25081, 59403, 22, 4192, 139, 225, 238, 311, 4464, 374, 16812, 52367, 67, 76,
    120, 16575, 39103, 277, 20800, 49410, 420, 25066, 56330, 48, 35343, 168, 247, 284, 332, 467, 16746, 53599,
    10, 116, 164, 216, 285, 334, 356, 16794, 63752, 40, 97, 126, 227, 6400, 314, 4544, 454, 16892,
    60815, 89, 131, 4272, 214, 18693, 50447, 16837, 62468, 56623, 84, 77, 16490, 39439, 279, 325, 371, 409,
    431, 49, 43, 16502, 36063, 213, 2306, 318, 370, 408, 25038, 54276, 20, 29, 103, 188, 252, 309,
    349, 485, 24940, 64007, 17, 35852, 161, 215, 281, 324, 355, 393, 415, 61935, 19, 59, 16518, 39951,
    2310, 322, 482, 361, 383, 85, 18443, 32911, 165, 16616, 46095, 433, 455, 509, 55743, 87, 98, 158,
    243, 43009, 45571, 2316, 333, 483, 24954, 55562, 53, 16497, 36991, 185, 203, 290, 343, 500, 16795, 51823,
    2, 2060, 135, 16558, 43279, 321, 450, 488, 8559, 56577, 9, 99, 159, 244, 2305, 315, 385, 391,
    16829, 63903, 55, 16412, 34159, 186, 204, 308, 347, 421, 16875, 58751, 54, 61, 119, 173, 205, 294,
    16734, 51343, 16842, 54367, 80, 34831, 166, 16633, 45103, 4560, 423, 16861, 60575, 39, 4208, 16525, 37599, 198,
    18692, 47727, 481, 360, 414, 64959, 86, 94, 156, 194, 16638, 45647, 401, 407, 25037, 59654, 23, 44,
    16492, 42255, 18697, 47279, 353, 502, 24973, 59910, 21, 45, 151, 189, 221, 310, 351, 501, 24956, 60679,
    65, 35087, 182, 201, 2318, 339, 452, 16747, 63583, 8, 130, 127, 16580, 41167, 16660, 50191, 389, 25035,
    60424, 56, 114, 111, 212, 4368, 298, 4528, 438, 16876, 64143, 51, 4240, 109, 226, 207, 312, 4480,
    390, 16828, 57487, 32, 36111, 40971, 219, 306, 344, 357, 16811, 53375, 82, 62, 122, 16593, 43055, 45407,
    418, 456, 510, 59599, 88, 146, 143, 228, 44289, 275, 319, 402, 440, 16878, 56511, 16457, 33794, 147,
    163, 246, 2312, 327, 387, 425, 447, 68, 2062, 136, 190, 16621, 47375, 466, 16888, 55855, 33, 27,
    102, 172, 44159, 291, 345, 373, 16827, 55423, 4, 37127, 133, 171, 251, 292, 346, 405, 16859, 59775,
    90, 117, 169, 234, 4400, 338, 436, 16890, 64607, 3, 60, 104, 16559, 39343, 2315, 330, 435, 489,
    511};
void build_schedule(Params& prm, int pairs) {
  for (int i = 0; i < kAttnUnits; i++) prm.blk[i] = (uint16_t)(i | 1 << 12);
  uint8_t delay[kMaxPairs] = {};
  static uint16_t lists[kMaxPairs][kMaxUnits];
  int n[kMaxPairs] = {};
  double t[kMaxPairs] = {};
  const double ta = 40.0, to = 59.0;
  for (int u = 0; u < kUnits; u++) {
    int p = 0;
    for (int q = 1; q < pairs; q++)
      if (t[q] < t[p] - 1e-9) p = q;
    uint16_t code;
    if (u < kAttnUnits) {
      code = (uint16_t)u;
    } else {
      const int o = u - kAttnUnits, g2 = o / 5, r = o % 5;
      code = (uint16_t)(0x800F | (r < 4 ? ((2 * g2 + (r >> 1)) << 2) | (r & 1) : ((2 * g2) << 2) | 2) << 8);
    }
    lists[p][n[p]++] = code;
    t[p] += u < kAttnUnits ? ta : to;
  }
  if (pairs == kTunedPairs) {
    for (int p = 0, o = 0; p < pairs; p++) {
      n[p] = kTunedLen[p];
      delay[p] = kTunedDelay[p];
      for (int i = 0; i < n[p]; i++) lists[p][i] = kTunedUnit[o++];
    }
    for (int i = 0; i < kAttnUnits; i++) prm.blk[i] = kTunedBlock[i];
  }
  int o = 0;
  for (int p = 0; p < pairs; p++) {
    prm.head[p] = o | n[p] << 10 | delay[p] << 15 | (uint32_t)(lists[p][0] & 511) << 23;
    for (int i = 0; i < n[p]; i++) prm.unit[o++] = lists[p][i];
  }
}

}

extern "C" void kernel_launch(void* const* d_in, const int* in_sizes, int n_in, void* d_out, int out_size) {
  (void)in_sizes; (void)n_in; (void)out_size;
  void* fnp = nullptr;
  cudaDriverEntryPointQueryResult qr;
  if (cudaGetDriverEntryPoint("cuTensorMapEncodeTiled", &fnp, cudaEnableDefault, &qr) != cudaSuccess || !fnp) return;
  EncodeFn fn = (EncodeFn)fnp;
  void* optr = nullptr;
  cudaGetSymbolAddress(&optr, g_o);
  Params prm;
  bool ok = true;
  for (int br = 0; br < 2; br++) {
    void* const* in = d_in + 5 * br;
    ok &= encode_2d(fn, &prm.x[br], in[0], (uint64_t)kB * kSq, kD, NQ);
    ok &= encode_kv(fn, &prm.kv[br], in[1]);
    ok &= encode_kv(fn, &prm.kv[2 + br], in[2]);
    ok &= encode_panels(fn, &prm.wq[br], in[3], kD, kH * kDh, 64);
    ok &= encode_panels(fn, &prm.wo[br], in[4], kH * kDh, kD, 64);
    prm.xp[br] = (const __nv_bfloat16*)in[0];
    prm.wp[br] = (const __nv_bfloat16*)in[3];
    prm.kp[br] = (const __nv_bfloat16*)in[1];
    prm.vp[br] = (const __nv_bfloat16*)in[2];
  }
  prm.op = (__nv_bfloat16*)d_out;
  ok &= encode_2d(fn, &prm.o_ld, optr, (uint64_t)kAttnUnits * 4 * kSq, 64, NQ, CU_TENSOR_MAP_SWIZZLE_NONE);
  ok &= encode_panels(fn, &prm.out, d_out, (uint64_t)kB * kSq, 2 * kD, ST_ROWS, 1);
  if (!ok) return;
  cudaFuncSetAttribute(mha_fused_kernel, cudaFuncAttributeMaxDynamicSharedMemorySize, SMEM_BYTES);
  cudaLaunchConfig_t cfg = {};
  cfg.gridDim = dim3(2);
  cfg.blockDim = dim3(384);
  cfg.dynamicSmemBytes = SMEM_BYTES;
  cfg.stream = cudaStreamPerThread;
  int pairs = 0;
  if (cudaOccupancyMaxActiveClusters(&pairs, mha_fused_kernel, &cfg) != cudaSuccess || pairs < 1) return;
  if (pairs > kMaxPairs) pairs = kMaxPairs;
  if (pairs < 24) return;
  build_schedule(prm, pairs);
  mha_fused_kernel<<<2 * pairs, 384, SMEM_BYTES, cudaStreamPerThread>>>(prm);
}
```

```cpp
#include <cuda_runtime.h>
#include <cuda_bf16.h>
#include <cuda.h>
#include <stdint.h>

namespace {

constexpr int kB = 16, kSq = 224, kD = 640, kH = 32, kSk = 1024, kDh = 128;
constexpr int kGroups = 2 * kB;
constexpr int kAttnUnits = kGroups * kH / 2;
constexpr int kOutUnits = kGroups * 5 / 2;
constexpr int kUnits = kAttnUnits + kOutUnits;
constexpr int kMaxUnits = kUnits + 64;
constexpr int kMaxPairs = 72;
constexpr int NQ = 112;
constexpr int PANEL = NQ * 128;
constexpr float kQScale = 0.08838834764831845f * 1.4426950408889634f;
constexpr int SLOT = 16384;
constexpr int NSLOT = 7;

constexpr int SM_PANEL = 0;
constexpr int SM_RING = SM_PANEL + 8 * PANEL;
constexpr int NBAR = NSLOT + 8;
constexpr int SM_RCP = SM_RING + NSLOT * SLOT;
constexpr int SM_BAR = SM_RCP + 640;
constexpr int SM_END = SM_BAR + 8 * (2 * NBAR + 12) + 32;
constexpr int SMEM_BYTES = SM_END + 1024;
static_assert(SM_RING % 1024 == 0 && PANEL % 1024 == 0, "swizzle alignment");
static_assert(SMEM_BYTES <= 232448, "smem");

struct Params {
  CUtensorMap x[2], wq[2], kv[4], wo[2];
  CUtensorMap o_ld, out;
  const __nv_bfloat16* xp[2];
  const __nv_bfloat16* wp[2];
  const __nv_bfloat16* kp[2];
  const __nv_bfloat16* vp[2];
  __nv_bfloat16* op;
  uint32_t head[kMaxPairs];
  uint16_t unit[kMaxUnits];
  uint16_t blk[kAttnUnits];
};

struct Unit {
  bool attn, mc;
  int g, hc;
  int h0, nslab;
};
__device__ __forceinline__ int unit_slabs(uint32_t u) {
  return (u & 0x8000u) ? 4 * ((u & 15) + 1 - ((u >> 4) & 15)) : kD / 64;
}
__device__ __forceinline__ Unit decode_unit(uint32_t u, uint32_t rank) {
  Unit r;
  r.attn = !(u & 0x8000u);
  r.nslab = unit_slabs(u);
  if (r.attn) {
    r.g = (u >> 4) & 31;
    r.hc = (u & 15) * 2 + rank;
    r.mc = true;
    r.h0 = 0;
  } else {
    const uint32_t t = (u >> 8) & 3;
    r.mc = t < 2;
    r.g = ((u >> 10) & 31) + (t < 2 ? 0 : rank);
    r.hc = t < 2 ? 2 * t + rank : 4;
    r.h0 = (u >> 4) & 15;
  }
  return r;
}

__device__ uint4 g_qrow[2 * kMaxPairs * 2 * 16 * 128];
__device__ unsigned int g_pc[128 * 16 * 2];
__device__ __nv_bfloat16 g_o[(size_t)kAttnUnits * kSq * 2 * kDh];
__device__ unsigned int g_ticket;
__device__ unsigned int g_rd[kAttnUnits];
__device__ unsigned int g_cnt[kAttnUnits];

constexpr int CREGS = 232, SM_OFF = -1, ST_ROWS = 56;
template <bool V>
struct BoolC {
  static constexpr bool value = V;
};
template <int V>
struct IntC {
  static constexpr int value = V;
};
template <int I, int N, class F>
__device__ __forceinline__ void static_for(F&& f) {
  if constexpr (I < N) {
    f(IntC<I>{});
    static_for<I + 1, N>(f);
  }
}
constexpr uint32_t kPat0 = 04321432100, kPat1 = 04302102100;
__host__ __device__ constexpr int x_pos(int pat, int k) { return ((pat == 0 ? kPat0 : kPat1) >> 3 * k) & 7; }
__host__ __device__ constexpr int x_off(int pat, int k) { return k == 0 ? 0 : x_off(pat, k - 1) + (x_pos(pat, k - 1) == 0 ? 3 : 1); }
__host__ __device__ constexpr int w_cut(int i) { return 56 * i / 5; }
__device__ __forceinline__ uint32_t unit_pattern(uint32_t u, uint32_t prev) {
  return (prev & 0x8000u) && unit_slabs(u) >= 10 ? kPat1 : kPat0;
}
__device__ __forceinline__ uint32_t next_pos(uint32_t pos, int k, uint32_t pat) {
  return k < 9 ? (pat >> (3 * k + 3)) & 7 : (pos & 3) + 1;
}
__device__ __forceinline__ uint32_t pick(bool c, uint32_t a, uint32_t b) {
  uint32_t r;
  asm("{\n.reg .pred p;\nsetp.ne.u32 p, %1, 0;\nselp.u32 %0, %2, %3, p;\n}" : "=r"(r) : "r"((uint32_t)c), "r"(a), "r"(b));
  return r;
}
__device__ __forceinline__ uint32_t ring_round(uint32_t i) { return (i * 9363u) >> 16; }
__device__ __forceinline__ uint32_t ring_slot(uint32_t i) { return i - NSLOT * ring_round(i); }
__device__ __forceinline__ uint32_t ring_par(uint32_t i) { return ring_round(i) & 1; }

__device__ __forceinline__ uint32_t smem_u32(const void* p) { return (uint32_t)__cvta_generic_to_shared(p); }
__device__ __forceinline__ void mbar_init(uint32_t bar, uint32_t cnt) {
  asm volatile("mbarrier.init.shared::cta.b64 [%0], %1;" ::"r"(bar), "r"(cnt));
}
__device__ __forceinline__ void mbar_arrive1_if(uint32_t bar, bool pred) {
  asm volatile("{\n.reg .pred p;\nsetp.ne.u32 p, %1, 0;\n@p mbarrier.arrive.shared::cta.b64 _, [%0];\n}" ::"r"(bar), "r"((uint32_t)pred)
               : "memory");
}
__device__ __forceinline__ void mbar_wait_warp(uint32_t bar, uint32_t parity) {
  asm volatile(
      "{\n.reg .pred p, q;\n.reg .u32 c;\n"
      "mov.u32 c, 0;\n"
      "SPIN:\n"
      "mbarrier.try_wait.parity.shared::cta.b64 p, [%0], %1;\n"
      "vote.sync.all.pred q, p, 0xffffffff;\n"
      "@q bra.uni DONE;\n"
      "add.u32 c, c, 1;\n"
      "setp.gt.u32 q, c, 0x1000000;\n"
      "@q trap;\n"
      "bra.uni SPIN;\n"
      "DONE:\n}" ::"r"(bar),
      "r"(parity)
      : "memory");
}
__device__ __forceinline__ uint32_t mbar_test(uint32_t bar, uint32_t parity) {
  uint32_t ok;
  asm volatile(
      "{\n.reg .pred p;\nmbarrier.test_wait.parity.shared::cta.b64 p, [%1], %2;\nselp.u32 %0, 1, 0, p;\n}"
      : "=r"(ok)
      : "r"(bar), "r"(parity)
      : "memory");
  return ok;
}
__device__ __forceinline__ uint32_t mbar_test_if(uint32_t bar, uint32_t parity, bool pred) {
  uint32_t ok;
  asm volatile(
      "{\n.reg .pred p, q;\nsetp.ne.u32 q, %3, 0;\nsetp.eq.u32 p, %3, 0;\n"
      "@q mbarrier.test_wait.parity.shared::cta.b64 p, [%1], %2;\nselp.u32 %0, 1, 0, p;\n}"
      : "=r"(ok)
      : "r"(bar), "r"(parity), "r"((uint32_t)pred)
      : "memory");
  return ok;
}
#define ELECTED "{\n.reg .pred e;\nelect.sync _|e, 0xffffffff;\n@e "
constexpr uint64_t kEvictFirst = 0x12F0000000000000ull, kEvictNormal = 0x1000000000000000ull;
__device__ __forceinline__ void flag_wait(const unsigned int* p, uint32_t target) {
  asm volatile(
      "{\n.reg .pred p, q;\n.reg .u32 c, v;\n"
      "mov.u32 c, 0;\n"
      "SPIN:\n"
      "ld.acquire.gpu.global.u32 v, [%0];\n"
      "setp.ge.u32 p, v, %1;\n"
      "vote.sync.all.pred q, p, 0xffffffff;\n"
      "@q bra.uni DONE;\n"
      "nanosleep.u32 200;\n"
      "add.u32 c, c, 1;\n"
      "setp.gt.u32 q, c, 0x1000000;\n"
      "@q trap;\n"
      "bra.uni SPIN;\n"
      "DONE:\n}" ::"l"(p),
      "r"(target)
      : "memory");
}
__device__ __forceinline__ uint32_t flags_wait(const unsigned int* p, uint32_t target, uint32_t need) {
  uint32_t m;
  asm volatile(
      "{\n.reg .pred p, q;\n.reg .u32 c, v;\n"
      "mov.u32 c, 0;\n"
      "SPIN:\n"
      "ld.acquire.gpu.global.u32 v, [%1];\n"
      "setp.ge.u32 p, v, %2;\n"
      "vote.sync.ballot.b32 %0, p, 0xffffffff;\n"
      "and.b32 v, %0, %3;\n"
      "setp.eq.u32 q, v, %3;\n"
      "@q bra.uni DONE;\n"
      "add.u32 c, c, 1;\n"
      "setp.gt.u32 q, c, 0x1000000;\n"
      "@q trap;\n"
      "bra.uni SPIN;\n"
      "DONE:\n"
      "fence.proxy.async.global;\n}"
      : "=&r"(m)
      : "l"(p), "r"(target), "r"(need)
      : "memory");
  return m;
}
__device__ __forceinline__ void e_arrive(uint32_t bar, uint32_t n) {
  asm volatile(ELECTED "mbarrier.arrive.shared::cta.b64 _, [%0], %1;\n}" ::"r"(bar), "r"(n) : "memory");
}
__device__ __forceinline__ void e_expect_tx(uint32_t bar, uint32_t bytes) {
  asm volatile(ELECTED "mbarrier.arrive.expect_tx.shared::cta.b64 _, [%0], %1;\n}" ::"r"(bar), "r"(bytes) : "memory");
}
__device__ __forceinline__ void tma_ld2(uint32_t dst, const CUtensorMap* m, int c0, int c1, uint32_t bar, uint64_t pol) {
  asm volatile(ELECTED
               "cp.async.bulk.tensor.2d.shared::cluster.global.mbarrier::complete_tx::bytes.L2::cache_hint [%0], [%1, {%3, %4}], "
               "[%2], %5;\n}" ::"r"(dst),
               "l"(m), "r"(bar), "r"(c0), "r"(c1), "l"(pol)
               : "memory");
}
__device__ __forceinline__ void tma_ld2_mc(uint32_t dst, const CUtensorMap* m, int c0, int c1, uint32_t bar, uint64_t pol) {
  asm volatile(ELECTED
               "cp.async.bulk.tensor.2d.shared::cluster.global.mbarrier::complete_tx::bytes.multicast::cluster.L2::cache_hint "
               "[%0], [%1, {%3, %4}], [%2], %5, %6;\n}" ::"r"(dst),
               "l"(m), "r"(bar), "r"(c0), "r"(c1), "h"((uint16_t)3), "l"(pol)
               : "memory");
}
__device__ __forceinline__ void tma_ld3(uint32_t dst, const CUtensorMap* m, int c1, int c2, uint32_t bar, uint64_t pol) {
  asm volatile(ELECTED
               "cp.async.bulk.tensor.3d.shared::cluster.global.mbarrier::complete_tx::bytes.L2::cache_hint [%0], [%1, {%3, %4, "
               "%5}], [%2], %6;\n}" ::"r"(dst),
               "l"(m), "r"(bar), "r"(0), "r"(c1), "r"(c2), "l"(pol)
               : "memory");
}
__device__ __forceinline__ void tma_ld4(uint32_t dst, const CUtensorMap* m, int c3, uint32_t bar, uint64_t pol) {
  asm volatile(ELECTED
               "cp.async.bulk.tensor.4d.shared::cluster.global.mbarrier::complete_tx::bytes.L2::cache_hint [%0], [%1, {%3, %3, "
               "%3, %4}], [%2], %5;\n}" ::"r"(dst),
               "l"(m), "r"(bar), "r"(0), "r"(c3), "l"(pol)
               : "memory");
}
__device__ __forceinline__ void tma_st3(const CUtensorMap* m, int c1, int c2, uint32_t src, bool add) {
  if (add)
    asm volatile(ELECTED "cp.reduce.async.bulk.tensor.3d.global.shared::cta.add.bulk_group [%0, {%2, %3, %4}], [%1];\n}" ::"l"(m), "r"(src),
                 "r"(0), "r"(c1), "r"(c2)
                 : "memory");
  else
    asm volatile(ELECTED "cp.async.bulk.tensor.3d.global.shared::cta.bulk_group [%0, {%2, %3, %4}], [%1];\n}" ::"l"(m), "r"(src), "r"(0),
                 "r"(c1), "r"(c2)
                 : "memory");
}
__device__ __forceinline__ void wgmma_fence() { asm volatile("wgmma.fence.sync.aligned;" ::: "memory"); }
__device__ __forceinline__ void wgmma_commit() { asm volatile("wgmma.commit_group.sync.aligned;" ::: "memory"); }
template <int N>
__device__ __forceinline__ void wgmma_wait() {
  asm volatile("wgmma.wait_group.sync.aligned %0;" ::"n"(N) : "memory");
}
template <int N>
__device__ __forceinline__ void wgmma_wait_pin(int never, int c) {
  asm volatile("{\n.reg .pred p;\nsetp.eq.u32 p, %1, %2;\nAGAIN:\nwgmma.wait_group.sync.aligned %0;\n@p bra.uni AGAIN;\n}" ::"n"(N),
               "r"(never), "r"(c)
               : "memory");
}
__device__ __forceinline__ void pin_order(int never, int c) {
  asm volatile("{\n.reg .pred p;\nsetp.eq.u32 p, %0, %1;\nAGAIN:\n@p nanosleep.u32 1;\n@p bra.uni AGAIN;\n}" ::"r"(never), "r"(c) : "memory");
}
template <int N>
__device__ __forceinline__ void fence_regs(float (&d)[N]) {
#pragma unroll
  for (int i = 0; i < N; i++) asm volatile("" : "+f"(d[i])::"memory");
}
__device__ __forceinline__ void fence_async_smem() { asm volatile("fence.proxy.async.shared::cta;" ::: "memory"); }
__device__ __forceinline__ void bar_sync(int id, int n) { asm volatile("bar.sync %0, %1;" ::"r"(id), "r"(n) : "memory"); }
__device__ __forceinline__ void bar_arrive(int id, int n) {
  asm volatile("bar.arrive %0, %1;" ::"r"(id), "r"(n) : "memory");
}
__device__ __forceinline__ void stsm_x4_t(uint32_t addr, uint32_t r0, uint32_t r1, uint32_t r2, uint32_t r3) {
  asm volatile("stmatrix.sync.aligned.m8n8.x4.trans.shared.b16 [%0], {%1, %2, %3, %4};" ::"r"(addr), "r"(r0), "r"(r1),
               "r"(r2), "r"(r3)
               : "memory");
}
__device__ __forceinline__ void stsm_x4_t_pin(uint32_t addr, uint32_t r0, uint32_t r1, uint32_t r2, uint32_t r3, int never, int c) {
  asm volatile(
      "{\n.reg .pred p;\nsetp.eq.u32 p, %5, %6;\nAGAIN:\n"
      "stmatrix.sync.aligned.m8n8.x4.trans.shared.b16 [%0], {%1, %2, %3, %4};\n@p bra.uni AGAIN;\n}" ::"r"(addr),
      "r"(r0), "r"(r1), "r"(r2), "r"(r3), "r"(never), "r"(c)
      : "memory");
}
__device__ __forceinline__ void stsm_x2_t(uint32_t addr, uint32_t r0, uint32_t r1) {
  asm volatile("stmatrix.sync.aligned.m8n8.x2.trans.shared.b16 [%0], {%1, %2};" ::"r"(addr), "r"(r0), "r"(r1) : "memory");
}
__device__ __forceinline__ void stsm_x2_t_pin(uint32_t addr, uint32_t r0, uint32_t r1, int never, int c) {
  asm volatile(
      "{\n.reg .pred p;\nsetp.eq.u32 p, %3, %4;\nAGAIN:\n"
      "stmatrix.sync.aligned.m8n8.x2.trans.shared.b16 [%0], {%1, %2};\n@p bra.uni AGAIN;\n}" ::"r"(addr),
      "r"(r0), "r"(r1), "r"(never), "r"(c)
      : "memory");
}
__device__ __forceinline__ uint32_t pack_bf16(float lo, float hi) {
  uint32_t r;
  asm("cvt.rn.bf16x2.f32 %0, %1, %2;" : "=r"(r) : "f"(hi), "f"(lo));
  return r;
}
__device__ __forceinline__ float ex2(float x) {
  float y;
  asm("ex2.approx.ftz.f32 %0, %1;" : "=f"(y) : "f"(x));
  return y;
}
__device__ __forceinline__ uint32_t mk_desc(uint32_t addr) { return (1u << 16) | ((addr & 0x3FFFFu) >> 4); }

template <int TA, int TB = 0, int KV = 0>
__device__ __forceinline__ void wgmma_n112(float (&d)[56], uint32_t descA, uint32_t descB, int scaleD) {
  asm volatile(
      "{\n.reg .pred p;\n.reg .b32 hi, hb;\n.reg .b64 da, db;\nsetp.ne.b32 p, %58, 0;\n"
      "mov.b32 hi, %62;\nmov.b32 hb, %61;\nmov.b64 da, {%56, hi};\nmov.b64 db, {%57, hb};\n"
      "wgmma.mma_async.sync.aligned.m64n112k16.f32.bf16.bf16 "
      "{%0, %1, %2, %3, %4, %5, %6, %7, %8, %9, %10, %11, %12, %13, "
      "%14, %15, %16, %17, %18, %19, %20, %21, %22, %23, %24, %25, %26, %27, "
      "%28, %29, %30, %31, %32, %33, %34, %35, %36, %37, %38, %39, %40, %41, "
      "%42, %43, %44, %45, %46, %47, %48, %49, %50, %51, %52, %53, %54, %55}, "
      "da, db, p, 1, 1, %59, %60;\n}\n"
      : "+f"(d[0]), "+f"(d[1]), "+f"(d[2]), "+f"(d[3]), "+f"(d[4]), "+f"(d[5]), "+f"(d[6]),
        "+f"(d[7]), "+f"(d[8]), "+f"(d[9]), "+f"(d[10]), "+f"(d[11]), "+f"(d[12]), "+f"(d[13]),
        "+f"(d[14]), "+f"(d[15]), "+f"(d[16]), "+f"(d[17]), "+f"(d[18]), "+f"(d[19]), "+f"(d[20]),
        "+f"(d[21]), "+f"(d[22]), "+f"(d[23]), "+f"(d[24]), "+f"(d[25]), "+f"(d[26]), "+f"(d[27]),
        "+f"(d[28]), "+f"(d[29]), "+f"(d[30]), "+f"(d[31]), "+f"(d[32]), "+f"(d[33]), "+f"(d[34]),
        "+f"(d[35]), "+f"(d[36]), "+f"(d[37]), "+f"(d[38]), "+f"(d[39]), "+f"(d[40]), "+f"(d[41]),
        "+f"(d[42]), "+f"(d[43]), "+f"(d[44]), "+f"(d[45]), "+f"(d[46]), "+f"(d[47]), "+f"(d[48]),
        "+f"(d[49]), "+f"(d[50]), "+f"(d[51]), "+f"(d[52]), "+f"(d[53]), "+f"(d[54]), "+f"(d[55])
      : "r"(descA), "r"(descB), "r"(scaleD), "n"(TA), "n"(TB), "n"(TB ? 8 : 0x40000040), "n"(KV ? 0x40000080 : 0x40000040));
}

template <int T>
__device__ __forceinline__ void pack_half(float (&pk)[56], const float (&a)[56]) {
#pragma unroll
  for (int i = 0; i < 28; i++) pk[28 * T + i] = __uint_as_float(pack_bf16(a[2 * i], a[2 * i + 1]));
}
template <int T>
__device__ __forceinline__ void fence_half(float (&pk)[56]) {
#pragma unroll
  for (int i = 0; i < 28; i++) asm volatile("" : "+f"(pk[28 * T + i])::"memory");
}
template <int T, int LO = 0, int HI = 7>
__device__ __forceinline__ void store_half(uint32_t addr, const float (&pk)[56]) {
#pragma unroll
  for (int q = LO; q < HI; q++) {
    const float* r = pk + 28 * T + 4 * q;
    stsm_x4_t(addr + T * PANEL + q * 2048, __float_as_uint(r[0]), __float_as_uint(r[1]), __float_as_uint(r[2]), __float_as_uint(r[3]));
  }
}

template <int T>
__device__ __forceinline__ void q_half(uint32_t addr, float (&pk)[56], const float (&a)[56], int never) {
#pragma unroll
  for (int q = 0; q < 7; q++) {
    uint32_t r[4];
#pragma unroll
    for (int i = 0; i < 4; i++) {
      r[i] = pack_bf16(a[8 * q + 2 * i] * kQScale, a[8 * q + 2 * i + 1] * kQScale);
      pk[28 * T + 4 * q + i] = __uint_as_float(r[i]);
      if (T == 0 && (i == 1 || (i == 3 && q == 6))) stsm_x2_t(addr + q * 2048 + (i >> 1) * 1024, r[i - 1], r[i]);
    }
    if (T == 0 && q < 6) stsm_x2_t_pin(addr + q * 2048 + 1024, r[2], r[3], never, 4 + 4 * q);
    if (T == 1 && q < 6) stsm_x4_t_pin(addr + PANEL + q * 2048, r[0], r[1], r[2], r[3], never, 30 + 2 * q);
    if (T == 1 && q == 6) stsm_x4_t(addr + PANEL + q * 2048, r[0], r[1], r[2], r[3]);
  }
}

__device__ __forceinline__ float bf_lo(uint32_t u) { return __uint_as_float(u << 16); }
__device__ __forceinline__ float bf_hi(uint32_t u) { return __uint_as_float(u & 0xFFFF0000u); }

__device__ __forceinline__ void fma8(float* o, float a, const uint4& w, float c) {
  o[0] = fmaf(a, bf_lo(w.x), o[0] * c), o[1] = fmaf(a, bf_hi(w.x), o[1] * c);
  o[2] = fmaf(a, bf_lo(w.y), o[2] * c), o[3] = fmaf(a, bf_hi(w.y), o[3] * c);
  o[4] = fmaf(a, bf_lo(w.z), o[4] * c), o[5] = fmaf(a, bf_hi(w.z), o[5] * c);
  o[6] = fmaf(a, bf_lo(w.w), o[6] * c), o[7] = fmaf(a, bf_hi(w.w), o[7] * c);
}
__device__ __forceinline__ void slow_rows(uint4* qrow, int tq, const __nv_bfloat16* xp, const __nv_bfloat16* wp,
                                          const __nv_bfloat16* kp, const __nv_bfloat16* vp, __nv_bfloat16* op) {
  if (tq >= NQ) return;
#pragma unroll 1
  for (int c = 0; c < 16; c++) {
    float q[8] = {};
#pragma unroll 1
    for (int k = 0; k < kD; k++)
      fma8(q, __bfloat162float(xp[tq * kD + k]), __ldg(reinterpret_cast<const uint4*>(wp + k * (kH * kDh)) + c), 1.f);
    qrow[c * 128] = make_uint4(pack_bf16(q[0] * kQScale, q[1] * kQScale), pack_bf16(q[2] * kQScale, q[3] * kQScale),
                               pack_bf16(q[4] * kQScale, q[5] * kQScale), pack_bf16(q[6] * kQScale, q[7] * kQScale));
  }
#pragma unroll 1
  for (int pass = 0; pass < 4; pass++) {
    float o[32] = {}, m = -INFINITY, l = 0.f;
#pragma unroll 1
    for (int key = 0; key < kSk; key++) {
      const uint4* kr = reinterpret_cast<const uint4*>(kp + key * kDh);
      const uint4* vr = reinterpret_cast<const uint4*>(vp + key * kDh) + 4 * pass;
      float s = 0.f;
#pragma unroll 1
      for (int c = 0; c < 16; c++) {
        const uint4 q = qrow[c * 128], k = __ldg(kr + c);
        s = fmaf(bf_lo(q.x), bf_lo(k.x), s); s = fmaf(bf_hi(q.x), bf_hi(k.x), s);
        s = fmaf(bf_lo(q.y), bf_lo(k.y), s); s = fmaf(bf_hi(q.y), bf_hi(k.y), s);
        s = fmaf(bf_lo(q.z), bf_lo(k.z), s); s = fmaf(bf_hi(q.z), bf_hi(k.z), s);
        s = fmaf(bf_lo(q.w), bf_lo(k.w), s); s = fmaf(bf_hi(q.w), bf_hi(k.w), s);
      }
      const float mn = fmaxf(m, s);
      const float ms = (mn == -INFINITY) ? 0.f : mn;
      const float corr = ex2(m - ms), p = ex2(s - ms);
      l = l * corr + p;
      m = mn;
      const float pb = __bfloat162float(__float2bfloat16(p));
#pragma unroll
      for (int c = 0; c < 4; c++) fma8(o + 8 * c, pb, __ldg(vr + c), corr);
    }
    const float sc = __fdividef(1.f, l);
    __nv_bfloat16* dst = op + (pass >> 1) * PANEL + (pass & 1) * 3584 + (tq >> 3) * 64 + (tq & 7);
#pragma unroll
    for (int d = 0; d < 32; d++) dst[(d >> 3) * 896 + (d & 7) * 8] = __float2bfloat16(o[d] * sc);
  }
}

__device__ __forceinline__ uint32_t launch_epoch() { return atomicAdd(&g_ticket, 1u) / gridDim.x; }

__global__ void __cluster_dims__(2, 1, 1) __launch_bounds__(384, 1) mha_fused_kernel(const __grid_constant__ Params prm) {
  extern __shared__ __align__(1024) unsigned char smem_raw[];

  const uint32_t sb = (smem_u32(smem_raw) + 1023u) & ~1023u;
  const uint32_t full0 = sb + SM_BAR, empty0 = full0 + 8 * NBAR, sfull0 = empty0 + 8 * NBAR;
  const uint32_t cred0 = sfull0 + 32, redo0 = cred0 + 64, epoch_addr = redo0 + 8, go_bar = redo0 + 16, ok_bar = redo0 + 24;
  const uint32_t rank = blockIdx.x & 1, pair = blockIdx.x >> 1;
  const uint32_t head = prm.head[pair];
  const int u_begin = head & 1023, u_end = u_begin + ((head >> 10) & 31);
  const uint32_t delay = ((head >> 15) & 255) * 256;
  const int tid = threadIdx.x;
  const int wid = __shfl_sync(0xffffffffu, tid >> 5, 0), wg = wid >> 2;

  if (wg == 2) {
    asm volatile("setmaxnreg.dec.sync.aligned.u32 %0;" ::"n"(504 - 2 * CREGS));
    const int warp = wid & 3, lane = tid & 31;
    bar_sync(0, 384);
    asm volatile("barrier.cluster.arrive.relaxed.aligned;" ::: "memory");
    if (warp < 3 && delay)
      asm volatile(
          "{\n.reg .pred p, q;\n.reg .u32 t0, t;\nmov.u32 t0, %%clock;\n"
          "SPIN:\nnanosleep.u32 100;\nmov.u32 t, %%clock;\nsub.u32 t, t, t0;\nsetp.lt.u32 p, t, %0;\n"
          "vote.sync.all.pred q, p, 0xffffffff;\n@q bra.uni SPIN;\n}" ::"r"(delay));
    auto slot_addr = [&](uint32_t i) { return sb + SM_RING + ring_slot(i) * SLOT; };
    auto full_bar = [&](uint32_t i) { return full0 + 8 * ring_slot(i); };
    const int count = (head >> 10) & 31;
    if (warp == 0) {
      uint32_t it = 6, prev = 0, code = head >> 23;
      auto acquire = [&](uint32_t i) { mbar_wait_warp(empty0 + 8 * ring_slot(i), ring_par(i) ^ 1); };
      uint32_t rblk = 0, rleft = 0;
      auto block_read = [&]() {
        asm volatile(ELECTED "red.relaxed.gpu.global.add.u32 [%0], 1;\n}" ::"l"(&g_rd[prm.blk[rblk] & 511]) : "memory");
        rblk++;
        rleft--;
      };
#pragma unroll 1
      for (int n = 1; n <= count; n++) {
        const uint32_t pat = unit_pattern(code, prev);
        const Unit u = decode_unit(code, rank);
        const int br = u.g >> 4;
        const CUtensorMap* mw = (u.attn ? prm.wq : prm.wo) + br;
        const int nslab = u.nslab;
#pragma unroll 1
        for (int k = n == 1 ? 2 : 0, pos = n == 1; k < nslab; k++) {
          const uint32_t i = it + (pos == 0);
          acquire(i);
          e_expect_tx(full_bar(i), SLOT);
          tma_ld3(slot_addr(i), mw, u.h0 * 256 + k * 64, u.hc * 2, full_bar(i), kEvictNormal);
          if (rleft && (k & 3) == 2 && k != 6) {
#pragma unroll 1
            do block_read();
            while (rleft && k == 2);
          }
          if (!u.attn && k == 4) rblk = u.g * 16 + u.h0, rleft = nslab >> 2;
          it = i + 1 + (pos == 0);
          pos = next_pos(pos, k, pat);
        }
        if (u.attn) {
          const int row0 = ((u.g & 15) * kH + u.hc) * kSk;
#pragma unroll 1
          for (int j = 0; j < kSk / 32; j++, it++) {
            acquire(it);
            e_expect_tx(full_bar(it), SLOT);
            const int isv = j == 31 || (j > 0 && !(j & 1));
            tma_ld4(slot_addr(it), &prm.kv[2 * isv + br], row0 / 8 + (((j + 1) >> 1) - isv) * 8, full_bar(it), kEvictFirst);
            if (j == kSk / 32 - 2) e_arrive(go_bar, 1);
          }
        }
        prev = code;
        code = prm.unit[u_begin + n];
      }
      if (rleft) {
        acquire(it + NSLOT - 1);
#pragma unroll 1
        while (rleft) block_read();
      }
    } else if (warp < 3) {
      asm volatile("barrier.cluster.wait.acquire.aligned;" ::: "memory");
      const int w = warp == 1 ? rank : rank ^ 1;
      uint32_t it = 6, nc = 0, pph = 0, go_ph = 0, prev = 0, code = head >> 23;
      const unsigned int* flags0 = g_cnt + (lane & 15);
      uint32_t peer_cred0;
      asm("mapa.shared::cluster.u32 %0, %1, %2;" : "=r"(peer_cred0) : "r"(cred0), "r"(rank ^ 1));
#pragma unroll 1
      for (int n = 1; n <= count; n++) {
        const uint32_t pat = unit_pattern(code, prev);
        Unit u = decode_unit(code, rank);
        const CUtensorMap* mx = u.attn ? &prm.x[u.g >> 4] : &prm.o_ld;
        const int nslab = u.nslab;
        const bool polls = !u.attn && (warp == 1 || !u.mc);
        uint32_t done = 0, ready = 0;
        if (polls) {
          asm volatile("ld.volatile.shared.u32 %0, [%1];" : "=r"(done) : "r"(epoch_addr) : "memory");
          done *= 2;
        }
        const unsigned int* flags;
        asm("add.u64 %0, %1, %2;" : "=l"(flags) : "l"(flags0), "l"((uint64_t)(uint32_t)(u.g * 64)));
        const uint64_t xpol = u.attn ? kEvictNormal : kEvictFirst;
        int xcol = n == 1 ? 128 : 0, xrow = (u.g & 15) * kSq + w * NQ;
#pragma unroll 1
        for (int k = n == 1 ? 2 : 0, pos = n == 1; k < nslab; k++) {
          if (polls && (k & 2) == 0) {
            const uint32_t hp = u.h0 + (k >> 2);
            if ((k & 1) == 0) {
              if (!(ready >> hp & 1)) ready = flags_wait(flags, done, 1u << hp);
              xrow = (prm.blk[u.g * 16 + hp] & 511) * (4 * kSq) + w * NQ;
            } else if (!(ready >> hp & 2)) {
              ready = flags_wait(flags, done, 0);
            }
          }
          const uint32_t i = it + 2 * w, q = pos - 1;
          const uint32_t fbar = full0 + 8 * (pos == 0 ? ring_slot(i) : NSLOT + 4 * w + q);
          const uint32_t dst = pos == 0 ? slot_addr(i) : sb + SM_PANEL + (4 * w + q) * PANEL;
          const uint32_t par = (pos == 0 ? ring_round(i) : pph >> q) & 1;
          pph ^= pos == 0 ? 0u : 1u << q;
          it += 1 + 2 * (pos == 0);
          pos = next_pos(pos, k, pat);
          mbar_wait_warp(fbar + 8 * NBAR, par ^ 1);
          e_expect_tx(fbar, PANEL);
          if (!u.mc) {
            tma_ld2(dst, mx, xcol, xrow, fbar, xpol);
          } else {
            if (warp == 1) {
              if (it > 10) mbar_wait_warp(cred0 + 8 * (nc & 7), (nc >> 3) & 1);
              tma_ld2_mc(dst, mx, xcol, xrow, fbar, xpol);
            } else if (it > 10) {
              asm volatile(ELECTED "mbarrier.arrive.shared::cluster.b64 _, [%0];\n}" ::"r"(peer_cred0 + 8 * (nc & 7)) : "memory");
            }
            nc += it > 10;
          }
          xcol += u.attn ? 64 : 0;
          xrow += u.attn ? 0 : kSq;
        }
        if (u.attn) {
          mbar_wait_warp(go_bar, go_ph);
          go_ph ^= 1;
          it += kSk / 32;
        }
        prev = code;
        code = prm.unit[u_begin + n];
      }
    } else {
      uint32_t epoch = 0, prev = 0;
      if (lane == 0) epoch = launch_epoch();
      epoch = __shfl_sync(0xffffffffu, epoch, 0);
      asm volatile("st.volatile.shared.u32 [%0], %1;" ::"r"(epoch_addr), "r"(epoch + 1) : "memory");
      auto publish = [&](unsigned int* p) {
        __syncwarp();
        asm volatile(ELECTED "red.release.gpu.global.add.u32 [%0], 1;\n}" ::"l"(p) : "memory");
      };
#pragma unroll 1
      for (int n = 0; n < count; n++) {
        const uint32_t code = prm.unit[u_begin + n], ph = n & 1;
        if (!(code & 0x8000u)) {
          const uint32_t blk = prm.blk[code & 511], gen = (blk >> 9) & 7;
          if (gen > 0) flag_wait(&g_rd[blk & 511], 5 * (epoch * (blk >> 12) + gen));
        }
        __syncwarp();
        e_arrive(ok_bar, 1);
        const uint32_t nx = n + 1 < count ? prm.unit[u_begin + n + 1] : 0;
        if (!(nx & 0x8000u) && (nx & 0x1800u)) {
          const Unit v = decode_unit(nx, rank);
          if (nx & 0x1000u) {
            const char* p = reinterpret_cast<const char*>(prm.xp[v.g >> 4] + ((v.g & 15) * kSq + rank * NQ) * kD) + lane * 128;
#pragma unroll 1
            for (int i = 0; i < NQ * kD * 2 / 4096; i++, p += 4096) {
              asm volatile("prefetch.global.L2 [%0];" ::"l"(p));
              __nanosleep(100);
            }
          }
          if (nx & 0x800u) {
            const char* p = reinterpret_cast<const char*>(prm.wp[v.g >> 4] + v.hc * kDh + (lane >> 1) * (kH * kDh)) + (lane & 1) * 128;
#pragma unroll 1
            for (int i = 0; i < kD / 16; i++, p += 16 * (kH * kDh * 2)) {
              asm volatile("prefetch.global.L2 [%0];" ::"l"(p));
              __nanosleep(100);
            }
          }
        }
        const bool clear = (code & 0xA000u) == 0x2000u;
        const uint32_t oc = clear ? nx : code;
        const Unit u = decode_unit(oc, rank);
        const int row = (u.g & 15) * kSq, cb = (u.g >> 4) * 10 + u.hc * 2;
        unsigned int* pc = g_pc + (oc >> 8 & 127) * 32 + rank;
        if (!(code & 0x8000u)) {
          if (clear) {
            uint4* o = reinterpret_cast<uint4*>(prm.op + (row + (lane >> 4)) * (2 * kD) + cb * 64) + (lane & 15);
#pragma unroll 1
            for (int r = 0; r < kSq / 2; r++, o += 4 * kD / 8) {
              *o = make_uint4(0, 0, 0, 0);
              __nanosleep(40);
            }
            publish(pc + 2 * (oc & 15));
          }
#pragma unroll 1
          for (int q = 0; q < 4; q++) mbar_wait_warp(sfull0 + 8 * q, ph);
          publish(&g_cnt[code & 511]);
        } else {
          const bool cleared = (prev & 0xA000u) == 0x2000u;
          if (u.h0) flag_wait(pc + 2 * (u.h0 - 1), epoch + 1);
          asm volatile("fence.proxy.async.global;" ::: "memory");
#pragma unroll 1
          for (int q = 0; q < 4; q++) {
            const int w = n + 1 < count ? q & 1 : q >> 1, t = n + 1 < count ? q >> 1 : q & 1;
            mbar_wait_warp(sfull0 + 8 * (2 * t + w), ph);
            fence_async_smem();
#pragma unroll 1
            for (int r = 0; r < NQ; r += ST_ROWS) {
              tma_st3(&prm.out, row + w * NQ + r, cb + t, sb + SM_PANEL + (4 * w + 2 + t) * PANEL + r * 128, u.h0 || cleared);
              asm volatile("cp.async.bulk.commit_group;" ::: "memory");
              if (n + 1 < count) asm volatile("cp.async.bulk.wait_group.read 0;" ::: "memory");
            }
            __syncwarp();
            e_arrive(empty0 + 8 * (NSLOT + 4 * w + 2 + t), 2);
          }
          if ((code & 15) != 15 && !cleared) {
            asm volatile("cp.async.bulk.wait_group 0;" ::: "memory");
            asm volatile("fence.proxy.async.global;" ::: "memory");
            publish(pc + 2 * (code & 15));
          }
        }
        prev = code;
      }
      asm volatile("cp.async.bulk.wait_group 0;" ::: "memory");
    }
  } else {
    const int tq = tid & 127, lane = tid & 31, warp = tq >> 5;
    if (tid == 0) {
#pragma unroll
      for (int i = 0; i < NBAR; i++) {
        mbar_init(full0 + 8 * i, 1);
        mbar_init(empty0 + 8 * i, 2);
      }
#pragma unroll
      for (int i = 0; i < 12; i++) mbar_init(sfull0 + 8 * i, i < 4 ? 4 : 1);
      mbar_init(go_bar, 1);
      mbar_init(ok_bar, 1);
      asm volatile("st.shared.v4.u32 [%0], {%1, %1, %1, %1};" ::"r"(redo0), "r"(0) : "memory");
      asm volatile("fence.mbarrier_init.release.cluster;" ::: "memory");
      fence_async_smem();
    }
    if (wid == 0) {
      __syncwarp();
      const Unit u = decode_unit(head >> 23, rank);
#pragma unroll
      for (int i = 0; i < 6; i++) {
        e_expect_tx(full0 + 8 * i, i % 3 == 1 ? SLOT : PANEL);
        if (i % 3 == 1) tma_ld3(sb + SM_RING + i * SLOT, &prm.wq[u.g >> 4], i / 3 * 64, u.hc * 2, full0 + 8 * i, kEvictNormal);
        else tma_ld2(sb + SM_RING + i * SLOT, &prm.x[u.g >> 4], i / 3 * 64, (u.g & 15) * kSq + i % 3 / 2 * NQ, full0 + 8 * i, kEvictNormal);
      }
    } else if (wid < 5) {
      asm volatile(ELECTED "prefetch.tensormap [%0];\n}" ::"l"(prm.x + 2 * (wid - 1) + (head >> 31)) : "memory");
    }
    bar_sync(0, 384);
    asm volatile("barrier.cluster.arrive.relaxed.aligned;" ::: "memory");
    asm volatile("setmaxnreg.inc.sync.aligned.u32 %0;" ::"n"(CREGS));
    const uint32_t stage = sb + SM_PANEL + wg * 4 * PANEL;
    const uint32_t st_q = __shfl_sync(
        0xffffffffu, stage + ((lane >> 4) * 8 + (lane & 7)) * 128 + (((2 * warp + ((lane >> 3) & 1)) ^ (lane & 7)) << 4), lane);
    const uint32_t st_p = st_q + 2 * PANEL;
    const uint32_t dq = mk_desc(stage), dring = mk_desc(sb + SM_RING);
    float acc[2][56], s[56] = {};
    const int never = (sb >> 24) & ~1u;
    uint32_t it = 0, pph = 0;
    auto wait_full = [&](uint32_t i) { mbar_wait_warp(full0 + 8 * ring_slot(i), ring_par(i)); };
    auto test = [&](uint32_t bar, uint32_t par) { return mbar_test_if(bar, par, warp == 0); };
    auto probe = [&](uint32_t i) { return test(full0 + 8 * ring_slot(i), ring_par(i)); };
    auto release = [&](uint32_t i) { mbar_arrive1_if(empty0 + 8 * ring_slot(i), tq == 0); };
    auto slot_desc = [&](uint32_t i) { return dring + ring_slot(i) * (SLOT >> 4); };
    if (wg == 1) bar_arrive(1, 256);

    struct Fin {
      uint32_t rp[16];
      char* dst;
    };
    uint32_t ps[14] = {};
    float l[28] = {};
    auto step_sums = [&]() {
#pragma unroll
      for (int g = 0; g < 14; g++) asm("add.rn.bf16x2 %0, %0, %1;" : "+r"(ps[g]) : "r"(pack_bf16(l[2 * g], l[2 * g + 1])));
#pragma unroll
      for (int q = 0; q < 3; q++) stsm_x4_t(st_p + q * 2048, ps[2 * q], ps[2 * q + 7], ps[2 * q + 1], ps[2 * q + 8]);
      stsm_x2_t(st_p + 3 * 2048, ps[6], ps[13]);
    };
    auto flag_bad = [&](bool bad) {
      asm volatile("{\n.reg .pred p;\nsetp.ne.u32 p, %1, 0;\n@p st.shared.u32 [%0], %1;\n}" ::"r"(redo0 + 4 * wg), "r"((uint32_t)bad)
                   : "memory");
    };
    auto step_finite = [&](bool live) {
      uint32_t z[4] = {0, 0, 0, 0};
#pragma unroll
      for (int i = 0; i < 28; i++)
        asm volatile("fma.rn.bf16x2 %0, %1, %2, %0;" : "+r"(z[i & 3]) : "r"(__float_as_uint(s[2 * i])), "r"(__float_as_uint(s[2 * i + 1])));
      asm volatile("add.rn.bf16x2 %0, %0, %1;" : "+r"(z[0]) : "r"(z[1]));
      asm volatile("add.rn.bf16x2 %0, %0, %1;" : "+r"(z[2]) : "r"(z[3]));
      asm volatile("add.rn.bf16x2 %0, %0, %1;" : "+r"(z[0]) : "r"(z[2]));
      flag_bad(live && (((z[0] & 0x7F807F80u) + 0x00800080u) & 0x80008000u));
    };
    auto rows_addr = [&]() {
      const uint32_t q = min(tq, NQ - 1), hi = q >= 56, n = q - 56 * hi;
      return stage + 2 * PANEL + n * 128 + ((hi ^ (n & 7)) << 4);
    };
    auto rows_load = [&](Fin& f, uint32_t a) {
#pragma unroll
      for (int c = 0; c < 4; c++)
        asm volatile("ld.shared.v4.u32 {%0, %1, %2, %3}, [%4];"
                     : "=r"(f.rp[4 * c]), "=r"(f.rp[4 * c + 1]), "=r"(f.rp[4 * c + 2]), "=r"(f.rp[4 * c + 3])
                     : "r"(a ^ (c << 5))
                     : "memory");
    };
    auto step_rows = [&](const Fin& f, bool live) {
      const uint32_t q = min(tq, NQ - 1);
      float t = 0.f, t2 = 0.f;
#pragma unroll
      for (int i = 0; i < 8; i++) {
        uint32_t v;
        asm("add.rn.bf16x2 %0, %1, %2;" : "=r"(v) : "r"(f.rp[2 * i]), "r"(f.rp[2 * i + 1]));
        t += bf_lo(v), t2 += bf_hi(v);
      }
      t += t2;
      float r;
      asm("rcp.approx.ftz.f32 %0, %1;" : "=f"(r) : "f"(t));
      asm volatile("st.shared.u16 [%0], %1;" ::"r"(sb + SM_RCP + wg * 320 + (q >> 1 & 3) * 80 + (q >> 3) * 4 + (q & 1) * 2),
                   "h"((uint16_t)pack_bf16(r, r))
                   : "memory");
      flag_bad(live && !(t >= 9.094947017729282e-13f && t <= 1.329227995784916e36f));
    };
    auto step_scales = [&](Fin& f) {
#pragma unroll
      for (int c = 0; c < 4; c++)
        asm volatile("ld.shared.v4.u32 {%0, %1, %2, %3}, [%4];"
                     : "=r"(f.rp[4 * c]), "=r"(f.rp[4 * c + 1]), "=r"(f.rp[4 * c + 2]), "=r"(f.rp[4 * c + 3])
                     : "r"(sb + SM_RCP + wg * 320 + (lane & 3) * 80 + c * 16)
                     : "memory");
    };
    auto o_base = [&](uint32_t u) {
      return reinterpret_cast<char*>(g_o) + (size_t)((((prm.blk[u & 511] & 511u) * 4 + rank * 2) * 2 + wg) * (uint32_t)PANEL);
    };
    auto step_write = [&](const Fin& f, int lo, int hi) {
#pragma unroll
      for (int i = lo; i < hi; i++) {
        uint32_t v = __float_as_uint(s[i]);
        asm("mul.rn.bf16x2 %0, %0, %1;" : "+r"(v) : "r"(f.rp[(i % 28) >> 1]));
        s[i] = __uint_as_float(v);
        asm volatile("st.global.u32 [%0], %1;" ::"l"(f.dst + (i / 28) * 2 * PANEL + (i & 1) * 1792 + ((i % 28) >> 1) * 128), "r"(v) : "memory");
      }
    };
    auto keep_alive = [&](int lo, int hi, int c) {
      if (never == c) {
#pragma unroll
        for (int i = lo; i < hi; i++) asm volatile("st.shared.f32 [%0], %1;" ::"r"(stage + 4 * i), "f"(s[i]) : "memory");
        pin_order(never, c);
      }
    };
    auto step_signal = [&](int t) {
      __syncwarp();
      mbar_arrive1_if(sfull0 + 8 * (2 * t + wg), lane == 0);
    };
    auto free_panel = [&](int q) { mbar_arrive1_if(empty0 + 8 * (NSLOT + 4 * wg + q), tq < 2); };
    auto read_verdict = [&]() {
      uint32_t redo;
      asm volatile("ld.shared.u32 %0, [%1];" : "=r"(redo) : "r"(redo0 + 4 * wg) : "memory");
      return redo;
    };
    auto step_redo = [&](uint32_t prev) {
      asm volatile("" : "+r"(prev));
      bar_sync(3 + wg, 128);
      if (tq == 0) asm volatile("st.shared.u32 [%0], %1;" ::"r"(redo0 + 4 * wg), "r"(0) : "memory");
      const Unit u = decode_unit(prev & 511, rank);
      const int br = u.g >> 4, b = u.g & 15;
      const size_t off = (size_t)(b * kH + u.hc) * kSk * kDh;
      slow_rows(g_qrow + (blockIdx.x * 2 + wg) * (16 * 128) + tq, tq, prm.xp[br] + (b * kSq + wg * NQ) * kD, prm.wp[br] + u.hc * kDh,
                prm.kp[br] + off, prm.vp[br] + off, reinterpret_cast<__nv_bfloat16*>(o_base(prev)));
#pragma unroll
      for (int i = 0; i < 56; i++) s[i] = 0.f;
    };
    auto issue_slab = [&](uint32_t da, uint32_t db, int accum, auto split, auto tb) {
      constexpr int TB = tb.value, KS = TB ? 224 : 2;
      if (TB) db += 111 << 16;
      if (split.value == 1) {
#pragma unroll
        for (int t = 0; t < 2; t++) {
#pragma unroll
          for (int kk = 0; kk < 4; kk++) {
            if (t == 1 && kk == 2) bar_arrive(2 - wg, 256);
            wgmma_n112<1, 0, 1>(acc[t], da + t * 64 + kk * 256, db + kk * KS, 1);
          }
          wgmma_commit();
        }
      } else {
#pragma unroll
        for (int kk = 0; kk < 4; kk++) {
          if (kk == 3) bar_arrive(2 - wg, 256);
          wgmma_n112<1, TB>(acc[0], da + kk * 128, db + kk * KS, kk > 0 ? 1 : accum);
          wgmma_n112<1, TB>(acc[1], da + 512 + kk * 128, db + kk * KS, kk > 0 ? 1 : accum);
        }
        wgmma_commit();
      }
    };

    uint32_t code = head >> 23, prev = 0, pend = 0, uph = 0;
    uint32_t da = slot_desc(1), db = slot_desc(2 * wg);
    auto next_unit = [&](bool block) {
      da = slot_desc(it + 1), db = slot_desc(it + 2 * wg);
      if (block) {
        if (!__all_sync(0xffffffffu, probe(it + 1) & probe(it + 2 * wg))) {
          wait_full(it + 1);
          wait_full(it + 2 * wg);
        }
      }
    };
    wait_full(1);
    wait_full(2 * wg);
    for (int left = (head >> 10) & 31; left > 0; left--) {
      const int ui = u_end - left;
      uint32_t nxt;
      bool defer;
      auto peek = [&]() {
        const uint32_t cur = prm.unit[ui];
        nxt = __shfl_sync(0xffffffffu, (uint32_t)prm.unit[ui + 1], 0);
        defer = left > 1 && (!(nxt & 0x8000u) || ((cur & 0x8000u) ? unit_slabs(nxt) >= 10 : cur & 0x4000u));
      };
      const bool out = code & 0x8000u;
      uint32_t rel = 0;
      auto retire = [&]() {
        wgmma_wait<0>();
        fence_regs(acc[0]);
        fence_regs(acc[1]);
        mbar_arrive1_if(rel, rel);
        rel = 0;
      };
      auto turn = [&](int accum, auto mode, auto tb, auto first) {
        bar_sync(1 + wg, 256);
        if (!first.value) retire();
        wgmma_fence();
        issue_slab(da, db, accum, mode, tb);
      };
      auto take_turn = [&](int accum, auto mode, auto first) {
        if (out) turn(accum, mode, IntC<1>{}, first);
        else turn(accum, mode, IntC<0>{}, first);
      };
      Fin f;
      take_turn(0, IntC<0>{}, BoolC<true>{});
      int k = 0;
      const bool staged = pend == 2;
      if (out ? pend == 1 : !staged) {
        uint32_t redo = 0;
        static_for<0, 8>([&](auto kc) {
          constexpr int k = kc.value;
          if (k > 0) take_turn(1, IntC<0>{}, BoolC<false>{});
          if (k >= 4) keep_alive(w_cut(k - 4), w_cut(k - 3), 62 + 2 * k);
          if (k == 2) step_scales(f);
          constexpr int p0 = x_pos(0, k), p1 = x_pos(0, k + 1), o0 = x_off(0, k), o1 = x_off(0, k + 1);
          const uint32_t rw = empty0 + 8 * ring_slot(it + o0 + (p0 == 0));
          const uint32_t rx = empty0 + 8 * (p0 == 0 ? ring_slot(it + o0 + 2 * wg) : NSLOT + 4 * wg + p0 - 1);
          const uint32_t wi = it + o1 + (p1 == 0), xi = it + o1 + 2 * wg;
          const uint32_t xbar = full0 + 8 * (p1 == 0 ? ring_slot(xi) : NSLOT + 4 * wg + p1 - 1);
          const uint32_t xpar = (p1 == 0 ? ring_round(xi) : pph >> (p1 == 0 ? 0 : p1 - 1)) & 1;
          if constexpr (p1 != 0) pph ^= 1u << (p1 - 1);
          uint32_t okp = probe(wi) & test(xbar, xpar);
          if (k == 2) okp &= test(ok_bar, uph ^ pend);
          rel = pick(tq == 0, rw, pick(tq < 3 && (k < 6 || out), rx, 0));
          if (k == 0) {
            uint32_t a = rows_addr();
            asm volatile("" : "+r"(a), "+r"(okp), "+r"(rel));
            if (pend) step_sums();
            bar_sync(3 + wg, 128);
            rows_load(f, a);
          }
          if (k == 1) {
            mbar_arrive1_if(empty0 + 8 * (NSLOT + 4 * wg + 2), tq < 2 && pend);
            step_rows(f, pend);
          }
          if (k == 2) {
            step_finite(pend);
            f.dst = o_base(prev) + warp * 3584 + lane * 4;
          }
          if (k == 6) redo = read_verdict();
          if (k >= 3 && pend) step_write(f, w_cut(k - 3), w_cut(k - 2));
          if (k == 7) {
            if (__any_sync(0xffffffffu, redo)) step_redo(prev);
            __syncwarp();
            mbar_arrive1_if(sfull0 + 8 * (2 * lane + wg), lane < 2 && pend);
          }
          const bool ok = __all_sync(0xffffffffu, okp);
          da = slot_desc(wi);
          db = p1 == 0 ? slot_desc(xi) : dq + (p1 - 1) * (PANEL >> 4);
          if (!ok) {
            retire();
            wait_full(wi);
            mbar_wait_warp(xbar, xpar);
            if (k == 2) mbar_wait_warp(ok_bar, uph ^ pend);
          }
        });
        k = 8;
        if (out) turn(1, IntC<0>{}, IntC<1>{}, BoolC<false>{});
      }
      const int nslab = unit_slabs(code);
      uint32_t pos = k ? 3 : 0, wi = it + (k ? 12 : 1), xbar = full0 + 8 * (k ? NSLOT + 4 * wg + 2 : ring_slot(it + 2 * wg));
      const int kend = nslab - 2;
      if (k < kend) {
        uint32_t r = it + (k ? 13 : 3);
        const uint32_t pat = staged ? kPat1 : kPat0;
        const uint32_t keep_pos = out ? 3 : 1;
        const int keep_k = out ? nslab - 4 : 5;
#pragma unroll 1
        while (true) {
          rel = pick(tq == 0, empty0 + 8 * ring_slot(wi), pick(tq < 3 && (pos < keep_pos || k < keep_k), xbar + 8 * NBAR, 0));
          pos = next_pos(pos, k, pat);
          const bool ring = pos == 0;
          const uint32_t i = r + 2 * wg, q = pos - 1;
          wi = ring ? r + 1 : r;
          xbar = full0 + 8 * (ring ? ring_slot(i) : NSLOT + 4 * wg + q);
          const uint32_t xpar = (ring ? ring_round(i) : pph >> q) & 1;
          da = slot_desc(wi);
          db = ring ? slot_desc(i) : dq + q * (PANEL >> 4);
          pph ^= ring ? 0u : 1u << q;
          r += ring ? 3 : 1;
          const bool ok = __all_sync(0xffffffffu, probe(wi) & test(xbar, xpar));
          if (staged && k < 2) {
            if (k == 0) {
              store_half<1, 0, 4>(st_p, s);
            } else {
              store_half<1, 4, 7>(st_p, s);
              step_signal(1);
            }
          }
          if (!ok) {
            retire();
            wait_full(wi);
            mbar_wait_warp(xbar, xpar);
          }
          if (++k == kend) break;
          take_turn(1, IntC<0>{}, BoolC<false>{});
        }
      }
      it += nslab + (staged ? 8 : 4);
      const uint32_t ql = out ? 1 : 3, xl = full0 + 8 * (NSLOT + 4 * wg + ql), pl = pph >> ql & 1, dl = slot_desc(it - 1);
      pph ^= 1u << ql;
      if (!__all_sync(0xffffffffu, probe(it - 1) & test(xl, pl))) {
        retire();
        wait_full(it - 1);
        mbar_wait_warp(xl, pl);
      }
      auto last_turn = [&](auto tb) {
        constexpr int TB = tb.value;
        bar_sync(1 + wg, 256);
        retire();
        wgmma_fence();
#pragma unroll
        for (int t = 0; t < 2; t++) {
#pragma unroll
          for (int kk = 0; kk < 8; kk++)
            wgmma_n112<1, TB>(acc[t], (kk < 4 ? da : dl) + t * 512 + (kk & 3) * 128,
                              db + t * never + (TB ? 111 << 16 : 0) + (kk >> 2) * (PANEL >> 4) + (kk & 3) * (TB ? 224 : 2), 1);
          wgmma_commit();
        }
        bar_arrive(2 - wg, 256);
      };
      const uint32_t rw2 = empty0 + 8 * pick(tq == 0, ring_slot(it - 2), ring_slot(it - 1));
      if (!out) {
        {
          last_turn(IntC<0>{});
          keep_alive(28, 56, 80);
          const bool ok = __all_sync(0xffffffffu, probe(it));
          rel = pick(tq < 2, rw2, 0);
          da = slot_desc(it);
          wgmma_wait<1>();
          fence_regs(acc[0]);
          q_half<0>(st_q, s, acc[0], never);
          wgmma_wait<0>();
          fence_regs(acc[1]);
          q_half<1>(st_q, s, acc[1], never);
          mbar_arrive1_if(rel, rel);
          if (!ok) wait_full(it);
        }
        fence_async_smem();
        auto issue_s = [&](uint32_t dk, int accum) {
          wgmma_fence();
#pragma unroll
          for (int kk = 0; kk < 8; kk++)
            wgmma_n112<0, 0, 1>(s, dk + (kk >> 2) * 64 + (kk & 3) * 2, dq + (kk >> 2) * (PANEL >> 4) + (kk & 3) * 2, kk > 0 ? 1 : accum);
          wgmma_commit();
        };
        auto add_sums = [&]() {
#pragma unroll
          for (int jj = 0; jj < 14; jj++)
            asm volatile("{\n.reg .b32 t;\nshl.b32 t, %2, 16;\nadd.f32 %0, %0, t;\nand.b32 t, %2, 0xffff0000;\nadd.f32 %1, %1, t;\n}"
                         : "+f"(l[2 * jj]), "+f"(l[2 * jj + 1])
                         : "r"(ps[jj]));
        };
        auto softmax = [&](uint32_t par, int pin0) {
          const uint32_t pa = st_p + par * PANEL;
#pragma unroll
          for (int i = 0; i < 4 + SM_OFF; i++) s[i] = ex2(s[i]);
#pragma unroll
          for (int jj = 0; jj < 14; jj++) {
#pragma unroll
            for (int i = 4 * jj + 4 + SM_OFF; i < 4 * jj + 8 + SM_OFF; i++)
              if (i < 56) s[i] = ex2(s[i]);
            const uint32_t p0 = pack_bf16(s[4 * jj], s[4 * jj + 1]), p1 = pack_bf16(s[4 * jj + 2], s[4 * jj + 3]);
            stsm_x2_t_pin(pa + jj * 1024, p0, p1, never, pin0);
            s[4 * jj] = __uint_as_float(p0), s[4 * jj + 1] = __uint_as_float(p1);
            asm("add.rn.bf16x2 %0, %1, %2;" : "=r"(ps[jj]) : "r"(p0), "r"(p1));
          }
        };
        bar_sync(1 + wg, 256);
        issue_s(da, never);
        bar_arrive(2 - wg, 256);
        {
#pragma unroll
          for (int i = 0; i < 28; i++) asm volatile("mov.b32 %0, 0;" : "=f"(l[i]));
          peek();
          const bool ok = __all_sync(0xffffffffu, probe(it + 1));
          da = slot_desc(it + 1);
          wgmma_wait_pin<0>(never, 180);
          fence_regs(s);
          release(it);
          softmax(0, 176);
          if (!ok) wait_full(it + 1);
        }
        it += 1;
#pragma unroll 1
        for (int j = 1; j < 16; j++) {
          fence_async_smem();
          bar_sync(1 + wg, 256);
          issue_s(da, 0);
          pin_order(never, 2 * j + 128);
          const uint32_t okv = mbar_test(full0 + 8 * ring_slot(it + 1), ring_par(it + 1));
          const uint32_t okk = probe(it + 2);
          da = slot_desc(it + 2);
          add_sums();
          const bool ok = __all_sync(0xffffffffu, okk);
          if (!__all_sync(0xffffffffu, okv)) wait_full(it + 1);
          {
            const uint32_t dv = slot_desc(it + 1), dp = dq + (3 - (j & 1)) * (PANEL >> 4);
            wgmma_fence();
#pragma unroll
            for (int kk = 0; kk < 4; kk++) {
              wgmma_n112<1, 0, 1>(acc[0], dv + kk * 256, dp + kk * 2, kk > 0 ? 1 : j > 1);
              wgmma_n112<1, 0, 1>(acc[1], dv + 64 + kk * 256, dp + kk * 2, kk > 0 ? 1 : j > 1);
            }
          }
          wgmma_commit();
          bar_arrive(2 - wg, 256);
          wgmma_wait<1>();
          fence_regs(s);
          release(it);
          softmax(j & 1, 2 * j + 192);
          wgmma_wait<0>();
          fence_regs(acc[0]);
          fence_regs(acc[1]);
          release(it + 1);
          it += 2;
          if (!ok) {
            wait_full(it);
          }
        }
        it += 1;
        fence_async_smem();
        bar_sync(1 + wg, 256);
        wgmma_fence();
        issue_slab(da, dq + 3 * (PANEL >> 4), 1, IntC<1>{}, IntC<0>{});
        pin_order(never, 182);
        mbar_arrive1_if(empty0 + 8 * (NSLOT + 4 * wg + (tq >> 1)), tq < 4);
        rel = pick(tq == 0, empty0 + 8 * ring_slot(it - 1), pick(tq < 3, empty0 + 8 * (NSLOT + 4 * wg + 3), 0));
        next_unit(defer);
        if (defer) {
          wgmma_wait<1>();
          fence_regs(acc[0]);
          pack_half<0>(s, acc[0]);
          fence_half<0>(s);
          wgmma_wait_pin<0>(never, 172);
          fence_regs(acc[1]);
          mbar_arrive1_if(rel, rel);
          pack_half<1>(s, acc[1]);
        }
        pend = 1;
      } else {
        last_turn(IntC<1>{});
        pin_order(never, 186);
        peek();
#pragma unroll
        for (int i = 0; i < 28; i++) ps[i >> 1] = 0, l[i] = 0.f;
        mbar_wait_warp(ok_bar, uph);
        next_unit(defer);
        rel = pick(tq < 2, rw2, pick(tq < 6, empty0 + 8 * (NSLOT + 4 * wg - 1 + (tq >> 1)), 0));
        wgmma_wait<1>();
        fence_regs(acc[0]);
        pack_half<0>(s, acc[0]);
        store_half<0>(st_p, s);
        step_signal(0);
        wgmma_wait<0>();
        fence_regs(acc[1]);
        mbar_arrive1_if(rel, rel);
        pack_half<1>(s, acc[1]);
        pend = 2;
      }
      if (!defer) {
        if (pend == 2) {
          store_half<1>(st_p, s);
        } else {
          step_sums();
          bar_sync(3 + wg, 128);
          rows_load(f, rows_addr());
          f.dst = o_base(code) + warp * 3584 + lane * 4;
          mbar_wait_warp(ok_bar, uph);
          step_rows(f, true);
          bar_sync(3 + wg, 128);
          step_scales(f);
          free_panel(2);
          retire();
          pack_half<0>(s, acc[0]);
          pack_half<1>(s, acc[1]);
          step_finite(true);
          step_write(f, 0, 28);
          bar_sync(3 + wg, 128);
          const uint32_t redo = read_verdict();
          step_write(f, 28, 56);
          if (__any_sync(0xffffffffu, redo)) step_redo(code);
          step_signal(0);
        }
        step_signal(1);
        pend = 0;
#pragma unroll
        for (int i = 0; i < 28; i++) ps[i >> 1] = 0, l[i] = 0.f;
        if (left > 1) {
          wait_full(it + 1);
          wait_full(it + 2 * wg);
        }
      }
      prev = code, code = nxt, uph ^= 1;
    }
    if (wg == 0) bar_sync(1, 256);
  }
}

typedef CUresult (*EncodeFn)(CUtensorMap*, CUtensorMapDataType, cuuint32_t, void*, const cuuint64_t*, const cuuint64_t*,
                             const cuuint32_t*, const cuuint32_t*, CUtensorMapInterleave, CUtensorMapSwizzle,
                             CUtensorMapL2promotion, CUtensorMapFloatOOBfill);

bool encode(EncodeFn fn, CUtensorMap* m, const void* ptr, int rank, const cuuint64_t* dims, const cuuint64_t* strides,
            const cuuint32_t* box, CUtensorMapL2promotion promo, CUtensorMapSwizzle swz = CU_TENSOR_MAP_SWIZZLE_128B) {
  const cuuint32_t es[4] = {1, 1, 1, 1};
  return fn(m, CU_TENSOR_MAP_DATA_TYPE_BFLOAT16, rank, const_cast<void*>(ptr), dims, strides, box, es,
            CU_TENSOR_MAP_INTERLEAVE_NONE, swz, promo,
            CU_TENSOR_MAP_FLOAT_OOB_FILL_NONE) == CUDA_SUCCESS;
}
bool encode_panels(EncodeFn fn, CUtensorMap* m, const void* ptr, uint64_t rows, uint64_t cols, uint32_t box_rows,
                   uint32_t box_blocks = 2) {
  const cuuint64_t dims[3] = {64, rows, cols / 64};
  const cuuint64_t strides[2] = {cols * 2, 128};
  const cuuint32_t box[3] = {64, box_rows, box_blocks};
  CUtensorMapL2promotion promo = CU_TENSOR_MAP_L2_PROMOTION_L2_128B;
  return encode(fn, m, ptr, 3, dims, strides, box, promo);
}
bool encode_kv(EncodeFn fn, CUtensorMap* m, const void* ptr) {
  const cuuint64_t dims[4] = {64, 8, 2, (uint64_t)kB * kH * kSk / 8};
  const cuuint64_t strides[3] = {kDh * 2, 128, 8 * kDh * 2};
  const cuuint32_t box[4] = {64, 8, 2, 8};
  CUtensorMapL2promotion promo = CU_TENSOR_MAP_L2_PROMOTION_L2_128B;
  return encode(fn, m, ptr, 4, dims, strides, box, promo);
}
bool encode_2d(EncodeFn fn, CUtensorMap* m, const void* ptr, uint64_t rows, uint64_t cols, uint32_t box_rows,
               CUtensorMapSwizzle swz = CU_TENSOR_MAP_SWIZZLE_128B) {
  const cuuint64_t dims[2] = {cols, rows};
  const cuuint64_t strides[1] = {cols * 2};
  const cuuint32_t box[2] = {64, box_rows};
  CUtensorMapL2promotion promo = CU_TENSOR_MAP_L2_PROMOTION_L2_128B;
  return encode(fn, m, ptr, 2, dims, strides, box, promo, swz);
}

constexpr int kTunedPairs = 66;
const uint16_t kTunedBlock[kAttnUnits] = {
    20480, 20486, 20492, 20498, 20504, 20510, 20516, 20522, 20528, 20534, 16444, 16450, 16456, 16462, 20996, 21002,
    20481, 20487, 20493, 20499, 20505, 20511, 20517, 20523, 20529, 20535, 16445, 16451, 16457, 16463, 20997, 21003,
    20482, 20488, 20494, 20500, 20506, 20512, 20518, 20524, 20530, 20536, 16446, 16452, 16458, 20992, 20998, 21004,
    20483, 20489, 20495, 20501, 20507, 20513, 20519, 20525, 20531, 20537, 16447, 16453, 16459, 20993, 20999, 21005,
    20484, 20490, 20496, 20502, 20508, 20514, 20520, 20526, 20532, 20538, 16448, 16454, 16460, 20994, 21000, 21006,
    20485, 20491, 20497, 20503, 20509, 20515, 20521, 20527, 20533, 20539, 16449, 16455, 16461, 20995, 21001, 21007,
    21008, 21012, 21016, 21020, 21024, 21028, 21032, 21036, 21040, 21044, 21048, 16956, 16960, 16964, 16968, 16972,
    21009, 21013, 21017, 21021, 21025, 21029, 21033, 21037, 21041, 21045, 21049, 16957, 16961, 16965, 16969, 16973,
    21010, 21014, 21018, 21022, 21026, 21030, 21034, 21038, 21042, 21046, 21050, 16958, 16962, 16966, 16970, 16974,
    21011, 21015, 21019, 21023, 21027, 21031, 21035, 21039, 21043, 21047, 21051, 16959, 16963, 16967, 16971, 16975,
    21504, 21506, 21508, 21510, 21512, 21514, 21516, 21518, 21520, 21522, 21524, 21526, 21528, 21530, 21532, 21534,
    21505, 21507, 21509, 21511, 21513, 21515, 21517, 21519, 21521, 21523, 21525, 21527, 21529, 21531, 21533, 21535,
    21536, 21540, 21544, 21548, 21552, 21556, 21560, 17468, 17472, 17476, 17480, 17484, 22016, 22020, 22024, 22028,
    21537, 21541, 21545, 21549, 21553, 21557, 21561, 17469, 17473, 17477, 17481, 17485, 22017, 22021, 22025, 22029,
    21538, 21542, 21546, 21550, 21554, 21558, 21562, 17470, 17474, 17478, 17482, 17486, 22018, 22022, 22026, 22030,
    21539, 21543, 21547, 21551, 21555, 21559, 21563, 17471, 17475, 17479, 17483, 17487, 22019, 22023, 22027, 22031,
    22032, 22034, 22036, 22038, 22040, 22042, 22044, 22046, 22048, 22050, 22052, 22054, 22056, 22058, 22060, 22062,
    22033, 22035, 22037, 22039, 22041, 22043, 22045, 22047, 22049, 22051, 22053, 22055, 22057, 22059, 22061, 22063,
    22064, 22066, 22068, 22070, 22072, 22074, 17980, 17982, 17984, 17986, 17988, 17990, 17992, 17994, 17996, 17998,
    22065, 22067, 22069, 22071, 22073, 22075, 17981, 17983, 17985, 17987, 17989, 17991, 17993, 17995, 17997, 17999,
    22528, 22529, 22530, 22531, 22532, 22533, 22534, 22535, 22536, 22537, 22538, 22539, 22540, 22541, 22542, 22543,
    22544, 22545, 22546, 22547, 22548, 22549, 22550, 22551, 22552, 22553, 22554, 22555, 22556, 22557, 22558, 22559,
    22560, 22570, 22580, 4178, 4188, 4198, 4208, 4218, 4228, 4238, 4248, 4258, 4268, 4278, 4288, 4298,
    22561, 22571, 22581, 4179, 4189, 4199, 4209, 4219, 4229, 4239, 4249, 4259, 4269, 4279, 4289, 4299,
    22562, 22572, 22582, 4180, 4190, 4200, 4210, 4220, 4230, 4240, 4250, 4260, 4270, 4280, 4290, 4300,
    22563, 22573, 22583, 4181, 4191, 4201, 4211, 4221, 4231, 4241, 4251, 4261, 4271, 4281, 4291, 4301,
    22564, 22574, 22584, 4182, 4192, 4202, 4212, 4222, 4232, 4242, 4252, 4262, 4272, 4282, 4292, 4302,
    22565, 22575, 22585, 4183, 4193, 4203, 4213, 4223, 4233, 4243, 4253, 4263, 4273, 4283, 4293, 4303,
    22566, 22576, 22586, 4184, 4194, 4204, 4214, 4224, 4234, 4244, 4254, 4264, 4274, 4284, 4294, 4304,
    22567, 22577, 22587, 4185, 4195, 4205, 4215, 4225, 4235, 4245, 4255, 4265, 4275, 4285, 4295, 4305,
    22568, 22578, 4176, 4186, 4196, 4206, 4216, 4226, 4236, 4246, 4256, 4266, 4276, 4286, 4296, 4306,
    22569, 22579, 4177, 4187, 4197, 4207, 4217, 4227, 4237, 4247, 4257, 4267, 4277, 4287, 4297, 4307};
const uint8_t kTunedLen[kTunedPairs] = {
    10, 10, 9, 9, 10, 10, 10, 11, 8, 10, 10, 11, 10, 9, 10, 10, 10, 9, 10, 12, 10, 11, 10, 10, 10, 10, 9, 10, 10, 10, 9, 10, 10,
    9, 10, 12, 10, 10, 9, 10, 9, 9, 10, 11, 10, 10, 9, 10, 10, 11, 9, 9, 9, 10, 11, 11, 10, 9, 10, 9, 10, 9, 10, 10, 10, 9};
const uint8_t kTunedDelay[kTunedPairs] = {
    0, 50, 117, 83, 48, 1, 7, 13, 109, 0, 42, 0, 85, 109, 13, 5, 56, 7, 13, 3, 13, 3,
    0, 13, 0, 0, 0, 7, 5, 0, 111, 0, 0, 1, 0, 3, 15, 0, 91, 27, 0, 3, 0, 0,
    0, 0, 93, 25, 9, 1, 62, 0, 25, 11, 80, 1, 0, 89, 0, 119, 1, 0, 0, 1, 1, 0};
const uint16_t kTunedUnit[] = {
    0, 36107, 127, 244, 2309, 319, 386, 392, 446, 64207, 72, 98, 158, 196, 2308, 301, 481, 471,
    509, 60863, 74, 133, 165, 232, 285, 4432, 404, 24986, 56330, 41, 99, 4272, 198, 280, 327, 355,
    361, 510, 56, 145, 142, 243, 275, 316, 465, 455, 493, 63679, 20, 16427, 33423, 181, 248, 2318,
    338, 436, 25002, 53770, 22, 16415, 33903, 188, 251, 16690, 49471, 486, 25084, 61446, 86, 95, 156, 194,
    238, 295, 20928, 52226, 360, 16798, 58559, 26, 116, 163, 16615, 46095, 16769, 51535, 57357, 51, 77, 153,
    20704, 43535, 323, 450, 456, 478, 60655, 40, 129, 126, 227, 2306, 315, 433, 423, 16845, 62127, 3,
    29, 105, 4288, 16589, 47620, 322, 434, 440, 8654, 54273, 57, 115, 161, 214, 18697, 47711, 403, 409,
    415, 62959, 42, 132, 179, 247, 2316, 333, 356, 24938, 64011, 23, 20592, 34191, 185, 250, 4400, 342,
    500, 25082, 55818, 85, 94, 139, 209, 253, 309, 4496, 358, 25067, 57608, 88, 114, 111, 212, 276,
    302, 354, 503, 16782, 56511, 6, 2063, 16539, 41487, 18696, 49679, 374, 16891, 61567, 55, 35343, 183, 249,
    286, 337, 16804, 57859, 25068, 62470, 37, 46, 16538, 38095, 16612, 40415, 44447, 317, 497, 487, 24942, 56580,
    39, 4224, 125, 210, 16638, 47106, 318, 16754, 54591, 479, 21, 30, 138, 4336, 16605, 48389, 328, 387,
    393, 399, 57583, 34, 76, 136, 191, 252, 308, 4464, 485, 25035, 59912, 7, 4192, 16493, 35023, 213,
    277, 321, 418, 25000, 60429, 49, 28, 104, 16574, 39327, 16667, 48495, 419, 425, 431, 67, 93, 16490,
    39176, 203, 289, 16727, 51721, 25066, 60682, 1, 35087, 39951, 2307, 300, 449, 439, 477, 64703, 38, 47,
    108, 225, 206, 294, 4512, 390, 24940, 64775, 69, 78, 123, 193, 237, 293, 4480, 501, 16859, 62591,
    50, 2061, 16536, 39439, 18694, 47567, 347, 405, 16779, 63855, 58, 148, 164, 200, 284, 334, 372, 16762,
    57935, 18, 16444, 38223, 242, 239, 312, 4592, 454, 16828, 58767, 16, 36870, 149, 168, 202, 2319, 341,
    484, 16858, 56671, 52, 16475, 33135, 16571, 43023, 4416, 402, 24984, 62733, 35, 61, 16521, 41279, 2305, 298,
    369, 359, 16765, 60063, 53, 62, 16491, 40962, 41218, 230, 16665, 45279, 346, 389, 24955, 61961, 71, 4240,
    141, 226, 207, 311, 4560, 422, 16780, 53391, 48, 38147, 130, 159, 229, 2311, 325, 482, 16872, 59439,
    89, 147, 162, 199, 282, 331, 467, 473, 495, 24, 113, 110, 211, 28944, 47371, 49157, 52543, 24988,
    58631, 81, 35855, 167, 16617, 45583, 52482, 371, 377, 383, 5, 2062, 16506, 42255, 278, 324, 466, 16856,
    54319, 17, 33797, 101, 180, 216, 2317, 335, 388, 24970, 63498, 19, 45, 121, 20688, 44035, 45068, 329,
    435, 441, 8639, 59393, 64, 34055, 16518, 40204, 6400, 16697, 50182, 51215, 16766, 55999, 66, 33029, 16501, 38927,
    273, 314, 401, 391, 16813, 55727, 10, 100, 178, 215, 2315, 332, 499, 25081, 55307, 87, 97, 157,
    195, 255, 297, 353, 470, 25052, 53510, 54, 63, 16508, 41023, 44111, 16687, 50303, 375, 16797, 53951, 68,
    2060, 151, 174, 220, 307, 16735, 51459, 376, 430, 55503, 16393, 37899, 4256, 245, 279, 326, 498, 504,
    494, 80, 32783, 166, 16585, 47167, 16733, 52287, 16781, 51887, 8, 37391, 182, 16601, 46351, 417, 407, 16829,
    61871, 70, 79, 140, 241, 222, 310, 4528, 406, 24956, 53255, 25, 16530, 36303, 16555, 42191, 274, 16683,
    49263, 502, 16749, 57759, 4, 27, 119, 16573, 44296, 290, 345, 16757, 54530, 25036, 59654, 2, 44, 120,
    175, 236, 292, 4448, 469, 16827, 53631, 73, 131, 177, 246, 2314, 330, 451, 457, 463, 33, 75,
    24711, 41995, 223, 296, 4576, 438, 16812, 64911, 90, 118, 169, 234, 4384, 340, 468, 25034, 64522, 36,
    16443, 37247, 170, 16603, 48143, 49410, 483, 489, 511, 82, 33287, 150, 16556, 43279, 50447, 16821, 63749, 367,
    32, 37126, 102, 184, 218, 287, 339, 452, 25018, 58378, 84, 16476, 36991, 186, 235, 305, 344, 357,
    24939, 61705, 83, 2059, 103, 173, 204, 291, 350, 453, 16811, 59775, 65, 34827, 143, 16581, 45327, 348,
    421, 24987, 55561};
void build_schedule(Params& prm, int pairs) {
  for (int i = 0; i < kAttnUnits; i++) prm.blk[i] = (uint16_t)(i | 1 << 12);
  uint8_t delay[kMaxPairs] = {};
  static uint16_t lists[kMaxPairs][kMaxUnits];
  int n[kMaxPairs] = {};
  double t[kMaxPairs] = {};
  const double ta = 40.0, to = 59.0;
  for (int u = 0; u < kUnits; u++) {
    int p = 0;
    for (int q = 1; q < pairs; q++)
      if (t[q] < t[p] - 1e-9) p = q;
    uint16_t code;
    if (u < kAttnUnits) {
      code = (uint16_t)u;
    } else {
      const int o = u - kAttnUnits, g2 = o / 5, r = o % 5;
      code = (uint16_t)(0x800F | (r < 4 ? ((2 * g2 + (r >> 1)) << 2) | (r & 1) : ((2 * g2) << 2) | 2) << 8);
    }
    lists[p][n[p]++] = code;
    t[p] += u < kAttnUnits ? ta : to;
  }
  if (pairs == kTunedPairs) {
    for (int p = 0, o = 0; p < pairs; p++) {
      n[p] = kTunedLen[p];
      delay[p] = kTunedDelay[p];
      for (int i = 0; i < n[p]; i++) lists[p][i] = kTunedUnit[o++];
    }
    for (int i = 0; i < kAttnUnits; i++) prm.blk[i] = kTunedBlock[i];
  }
  int o = 0;
  for (int p = 0; p < pairs; p++) {
    prm.head[p] = o | n[p] << 10 | delay[p] << 15 | (uint32_t)(lists[p][0] & 511) << 23;
    for (int i = 0; i < n[p]; i++) prm.unit[o++] = lists[p][i];
  }
}

}

extern "C" void kernel_launch(void* const* d_in, const int* in_sizes, int n_in, void* d_out, int out_size) {
  (void)in_sizes; (void)n_in; (void)out_size;
  void* fnp = nullptr;
  cudaDriverEntryPointQueryResult qr;
  if (cudaGetDriverEntryPoint("cuTensorMapEncodeTiled", &fnp, cudaEnableDefault, &qr) != cudaSuccess || !fnp) return;
  EncodeFn fn = (EncodeFn)fnp;
  void* optr = nullptr;
  cudaGetSymbolAddress(&optr, g_o);
  Params prm;
  bool ok = true;
  for (int br = 0; br < 2; br++) {
    void* const* in = d_in + 5 * br;
    ok &= encode_2d(fn, &prm.x[br], in[0], (uint64_t)kB * kSq, kD, NQ);
    ok &= encode_kv(fn, &prm.kv[br], in[1]);
    ok &= encode_kv(fn, &prm.kv[2 + br], in[2]);
    ok &= encode_panels(fn, &prm.wq[br], in[3], kD, kH * kDh, 64);
    ok &= encode_panels(fn, &prm.wo[br], in[4], kH * kDh, kD, 64);
    prm.xp[br] = (const __nv_bfloat16*)in[0];
    prm.wp[br] = (const __nv_bfloat16*)in[3];
    prm.kp[br] = (const __nv_bfloat16*)in[1];
    prm.vp[br] = (const __nv_bfloat16*)in[2];
  }
  prm.op = (__nv_bfloat16*)d_out;
  ok &= encode_2d(fn, &prm.o_ld, optr, (uint64_t)kAttnUnits * 4 * kSq, 64, NQ, CU_TENSOR_MAP_SWIZZLE_NONE);
  ok &= encode_panels(fn, &prm.out, d_out, (uint64_t)kB * kSq, 2 * kD, ST_ROWS, 1);
  if (!ok) return;
  cudaFuncSetAttribute(mha_fused_kernel, cudaFuncAttributeMaxDynamicSharedMemorySize, SMEM_BYTES);
  cudaLaunchConfig_t cfg = {};
  cfg.gridDim = dim3(2);
  cfg.blockDim = dim3(384);
  cfg.dynamicSmemBytes = SMEM_BYTES;
  cfg.stream = cudaStreamPerThread;
  int pairs = 0;
  if (cudaOccupancyMaxActiveClusters(&pairs, mha_fused_kernel, &cfg) != cudaSuccess || pairs < 1) return;
  if (pairs > kMaxPairs) pairs = kMaxPairs;
  if (pairs < 24) return;
  build_schedule(prm, pairs);
  mha_fused_kernel<<<2 * pairs, 384, SMEM_BYTES, cudaStreamPerThread>>>(prm);
}
```
